```python
import torch

def _softmax(x, axis=-1):
    return torch.softmax(x, dim=axis)
def _gelu(x):
    return torch.nn.functional.gelu(x, approximate="tanh")
def _silu(x):
    return torch.nn.functional.silu(x)
def _sigmoid(x):
    return torch.sigmoid(x)
def _layernorm(x, axis=-1, eps=1e-5):
    m = x.mean(dim=axis, keepdim=True)
    v = x.var(dim=axis, keepdim=True, unbiased=False)
    return (x - m) / torch.sqrt(v + eps)
def _scatter_add(tgt, idx, src, axis=0):
    return tgt.clone().index_add_(axis, idx, src)
def _segment_sum(src, seg, n):
    out = torch.zeros((n,) + src.shape[1:], dtype=src.dtype)
    return out.index_add_(0, seg, src)
def _pad(x, pw):
    flat = tuple(v for pair in reversed(pw) for v in pair)
    return torch.nn.functional.pad(x, flat)

kernel_name = 'standalone__normalfloat_lut_codebook_lookup__prompt'

def setup_inputs():

    _w = (lambda a: (lambda t: t.to(torch.bfloat16) if t.is_floating_point() else t)(torch.as_tensor(a)))
    B, S, D, F = 1, 2048, 1024, 3584
    G = -1 if -1 > 0 else D
    D = (D // G) * G
    ng = D // G
    nf4 = torch.tensor([
        -1.0, -0.6961928009986877, -0.5250730514526367, -0.39491748809814453,
        -0.28444138169288635, -0.18477343022823334, -0.09105003625154495, 0.0,
        0.07958029955625534, 0.16093020141124725, 0.24611230194568634, 0.33791524171829224,
        0.44070982933044434, 0.5626170039176941, 0.7229568362236023, 1.0
    ], dtype=float)
    qw = torch.randint(0, 16, (D, F)).to(torch.int64)
    absmax = (torch.abs((lambda *s: torch.randn(*s, dtype=torch.bfloat16) * 0.05)(ng, F)) + 0.01).to(float)
    return {
        "x": _w((lambda *s: torch.randn(*s, dtype=torch.bfloat16) * 0.05)(B, S, D)),
        "qw": _w(qw),
        "codebook": _w(nf4),
        "absmax": _w(absmax),
    }

def reference(x, qw, codebook, absmax):
    B, S, D = x.shape
    ng, F = absmax.shape
    G = D // ng
    w_nf = codebook[qw]
    s = (lambda x, n, axis: torch.repeat_interleave(x, n, dim=axis))(absmax, G, axis=0)
    w = (lambda x, dt: x.to(dt))(w_nf * s, x.dtype)
    return torch.einsum("bsd,df->bsf", x, w)
```

```cpp
#include <cuda_runtime.h>
#include <cuda_bf16.h>
#include <cuda.h>
#include <stdint.h>

namespace {

constexpr int M = 2048, N = 3584, K = 1024;
constexpr int BM = 128, BN = 224, BK = 64, KB = K / BK, STAGES = 4, NBLK = 2 * KB;
constexpr int XB = BM * BK * 2, WB = BN * BK * 2, STB = XB + WB, WH = WB / 2;
constexpr int EPI = 24576, SLOTB = 3584;
constexpr int SMEM = STAGES * STB + EPI + 4 * SLOTB + 512 + 1024;
constexpr int REG_CONSUMER = 208, REG_SIDE = 88;
constexpr int T_XPF0 = 1000, T_XPF = 200, T_JOB1_DELAY = 450, T_JOB2 = 5000, T_BLOCK = 800;

__device__ __align__(1024) unsigned char g_scratch[(size_t)K * N * 2 + 2048];

template <int OFF>
__device__ __forceinline__ void wgmma_n224(float (&d)[112], uint64_t da, uint64_t db, int scale_d) {
  asm volatile("{\n.reg .pred p;\nsetp.ne.b32 p, %114, 0;\n"
      "wgmma.mma_async.sync.aligned.m64n224k16.f32.bf16.bf16 {"
      "%0, %1, %2, %3, %4, %5, %6, %7, %8, %9, %10, %11, %12, %13, %14, %15, "
      "%16, %17, %18, %19, %20, %21, %22, %23, %24, %25, %26, %27, %28, %29, %30, %31, "
      "%32, %33, %34, %35, %36, %37, %38, %39, %40, %41, %42, %43, %44, %45, %46, %47, "
      "%48, %49, %50, %51, %52, %53, %54, %55, %56, %57, %58, %59, %60, %61, %62, %63, "
      "%64, %65, %66, %67, %68, %69, %70, %71, %72, %73, %74, %75, %76, %77, %78, %79, "
      "%80, %81, %82, %83, %84, %85, %86, %87, %88, %89, %90, %91, %92, %93, %94, %95, "
      "%96, %97, %98, %99, %100, %101, %102, %103, %104, %105, %106, %107, %108, %109, %110, %111"
      "}, %112, %113, p, 1, 1, 0, 1;\n}\n"
      : "+f"(d[OFF+0]), "+f"(d[OFF+1]), "+f"(d[OFF+2]), "+f"(d[OFF+3]), "+f"(d[OFF+4]), "+f"(d[OFF+5]), "+f"(d[OFF+6]), "+f"(d[OFF+7]),
      "+f"(d[OFF+8]), "+f"(d[OFF+9]), "+f"(d[OFF+10]), "+f"(d[OFF+11]), "+f"(d[OFF+12]), "+f"(d[OFF+13]), "+f"(d[OFF+14]), "+f"(d[OFF+15]),
      "+f"(d[OFF+16]), "+f"(d[OFF+17]), "+f"(d[OFF+18]), "+f"(d[OFF+19]), "+f"(d[OFF+20]), "+f"(d[OFF+21]), "+f"(d[OFF+22]), "+f"(d[OFF+23]),
      "+f"(d[OFF+24]), "+f"(d[OFF+25]), "+f"(d[OFF+26]), "+f"(d[OFF+27]), "+f"(d[OFF+28]), "+f"(d[OFF+29]), "+f"(d[OFF+30]), "+f"(d[OFF+31]),
      "+f"(d[OFF+32]), "+f"(d[OFF+33]), "+f"(d[OFF+34]), "+f"(d[OFF+35]), "+f"(d[OFF+36]), "+f"(d[OFF+37]), "+f"(d[OFF+38]), "+f"(d[OFF+39]),
      "+f"(d[OFF+40]), "+f"(d[OFF+41]), "+f"(d[OFF+42]), "+f"(d[OFF+43]), "+f"(d[OFF+44]), "+f"(d[OFF+45]), "+f"(d[OFF+46]), "+f"(d[OFF+47]),
      "+f"(d[OFF+48]), "+f"(d[OFF+49]), "+f"(d[OFF+50]), "+f"(d[OFF+51]), "+f"(d[OFF+52]), "+f"(d[OFF+53]), "+f"(d[OFF+54]), "+f"(d[OFF+55]),
      "+f"(d[OFF+56]), "+f"(d[OFF+57]), "+f"(d[OFF+58]), "+f"(d[OFF+59]), "+f"(d[OFF+60]), "+f"(d[OFF+61]), "+f"(d[OFF+62]), "+f"(d[OFF+63]),
      "+f"(d[OFF+64]), "+f"(d[OFF+65]), "+f"(d[OFF+66]), "+f"(d[OFF+67]), "+f"(d[OFF+68]), "+f"(d[OFF+69]), "+f"(d[OFF+70]), "+f"(d[OFF+71]),
      "+f"(d[OFF+72]), "+f"(d[OFF+73]), "+f"(d[OFF+74]), "+f"(d[OFF+75]), "+f"(d[OFF+76]), "+f"(d[OFF+77]), "+f"(d[OFF+78]), "+f"(d[OFF+79]),
      "+f"(d[OFF+80]), "+f"(d[OFF+81]), "+f"(d[OFF+82]), "+f"(d[OFF+83]), "+f"(d[OFF+84]), "+f"(d[OFF+85]), "+f"(d[OFF+86]), "+f"(d[OFF+87]),
      "+f"(d[OFF+88]), "+f"(d[OFF+89]), "+f"(d[OFF+90]), "+f"(d[OFF+91]), "+f"(d[OFF+92]), "+f"(d[OFF+93]), "+f"(d[OFF+94]), "+f"(d[OFF+95]),
      "+f"(d[OFF+96]), "+f"(d[OFF+97]), "+f"(d[OFF+98]), "+f"(d[OFF+99]), "+f"(d[OFF+100]), "+f"(d[OFF+101]), "+f"(d[OFF+102]), "+f"(d[OFF+103]),
      "+f"(d[OFF+104]), "+f"(d[OFF+105]), "+f"(d[OFF+106]), "+f"(d[OFF+107]), "+f"(d[OFF+108]), "+f"(d[OFF+109]), "+f"(d[OFF+110]), "+f"(d[OFF+111])
      : "l"(da), "l"(db), "r"(scale_d));
}

__device__ __forceinline__ uint32_t smem_u32(const void* p) { return (uint32_t)__cvta_generic_to_shared(p); }
__device__ __forceinline__ void mbar_init(uint32_t bar, uint32_t cnt) {
  asm volatile("mbarrier.init.shared::cta.b64 [%0], %1;" ::"r"(bar), "r"(cnt) : "memory");
}
__device__ __forceinline__ void mbar_expect_tx(uint32_t bar, uint32_t bytes) {
  asm volatile("mbarrier.arrive.expect_tx.shared::cta.b64 _, [%0], %1;" ::"r"(bar), "r"(bytes) : "memory");
}
__device__ __forceinline__ void mbar_arrive(uint32_t bar) {
  asm volatile("mbarrier.arrive.shared::cta.b64 _, [%0];" ::"r"(bar) : "memory");
}
__device__ __forceinline__ void mbar_arrive_remote(uint32_t cluster_addr) {
  asm volatile("mbarrier.arrive.shared::cluster.b64 _, [%0];" ::"r"(cluster_addr) : "memory");
}
__device__ __forceinline__ void mbar_wait(uint32_t bar, uint32_t parity) {
  asm volatile(
      "{\n.reg .pred p;\n.reg .u32 n;\nmov.u32 n, 0;\n"
      "LAB_WAIT:\nmbarrier.try_wait.parity.shared::cta.b64 p, [%0], %1;\n@p bra LAB_DONE;\n"
      "add.u32 n, n, 1;\nsetp.lt.u32 p, n, 1048576;\n@p bra LAB_WAIT;\ntrap;\nLAB_DONE:\n}" ::"r"(bar), "r"(parity) : "memory");
}
__device__ __forceinline__ void tma_load_2d(uint32_t dst, const CUtensorMap* m, int c0, int c1, uint32_t bar) {
  asm volatile("cp.async.bulk.tensor.2d.shared::cluster.global.mbarrier::complete_tx::bytes [%0], [%1, {%3, %4}], [%2];"
               ::"r"(dst), "l"(m), "r"(bar), "r"(c0), "r"(c1) : "memory");
}
__device__ __forceinline__ void bulk_load(uint32_t dst, const void* src, uint32_t bytes, uint32_t bar) {
  asm volatile("cp.async.bulk.shared::cluster.global.mbarrier::complete_tx::bytes [%0], [%1], %2, [%3];"
               ::"r"(dst), "l"(src), "r"(bytes), "r"(bar) : "memory");
}
__device__ __forceinline__ void bulk_load_multicast(uint32_t dst, const void* src, uint32_t bytes, uint32_t bar, uint16_t mask) {
  asm volatile("cp.async.bulk.shared::cluster.global.mbarrier::complete_tx::bytes.multicast::cluster [%0], [%1], %2, [%3], %4;"
               ::"r"(dst), "l"(src), "r"(bytes), "r"(bar), "h"(mask) : "memory");
}
__device__ __forceinline__ void tma_store_2d(const CUtensorMap* m, uint32_t src, int c0, int c1, uint64_t pol) {
  asm volatile("cp.async.bulk.tensor.2d.global.shared::cta.bulk_group.L2::cache_hint [%0, {%2, %3}], [%1], %4;"
               ::"l"(m), "r"(src), "r"(c0), "r"(c1), "l"(pol) : "memory");
}
__device__ __forceinline__ void bulk_commit() { asm volatile("cp.async.bulk.commit_group;" ::: "memory"); }
template <int NG> __device__ __forceinline__ void bulk_wait_read() { asm volatile("cp.async.bulk.wait_group.read %0;" ::"n"(NG) : "memory"); }
template <int NG> __device__ __forceinline__ void bulk_wait() { asm volatile("cp.async.bulk.wait_group %0;" ::"n"(NG) : "memory"); }
__device__ __forceinline__ void fence_async_smem() { asm volatile("fence.proxy.async.shared::cta;" ::: "memory"); }
__device__ __forceinline__ void wg_fence() { asm volatile("wgmma.fence.sync.aligned;" ::: "memory"); }
__device__ __forceinline__ void wg_commit() { asm volatile("wgmma.commit_group.sync.aligned;" ::: "memory"); }
template <int NG> __device__ __forceinline__ void wg_wait() { asm volatile("wgmma.wait_group.sync.aligned %0;" ::"n"(NG) : "memory"); }
__device__ __forceinline__ void cluster_arrive() { asm volatile("barrier.cluster.arrive.relaxed.aligned;" ::: "memory"); }
__device__ __forceinline__ void cluster_wait() { asm volatile("barrier.cluster.wait.aligned;" ::: "memory"); }
template <int R> __device__ __forceinline__ void reg_inc() { asm volatile("setmaxnreg.inc.sync.aligned.u32 %0;" ::"n"(R)); }
template <int R> __device__ __forceinline__ void reg_dec() { asm volatile("setmaxnreg.dec.sync.aligned.u32 %0;" ::"n"(R)); }
__device__ __forceinline__ void wg_sync(int wg) {
  if (wg == 0) asm volatile("bar.sync 1, 128;" ::: "memory"); else asm volatile("bar.sync 2, 128;" ::: "memory");
}
__device__ __forceinline__ uint32_t mapa(uint32_t a, uint32_t cta) {
  uint32_t r; asm("mapa.shared::cluster.u32 %0, %1, %2;" : "=r"(r) : "r"(a), "r"(cta)); return r;
}
__device__ __forceinline__ uint64_t make_desc(uint32_t addr, uint32_t lbo, uint32_t sbo, uint32_t mode) {
  return (uint64_t)((addr & 0x3FFFF) >> 4) | ((uint64_t)(lbo >> 4) << 16) | ((uint64_t)(sbo >> 4) << 32) | ((uint64_t)mode << 62);
}
__device__ __forceinline__ uint32_t pack_bf16(float lo, float hi) {
  uint32_t r; asm("cvt.rn.bf16x2.f32 %0, %1, %2;" : "=r"(r) : "f"(hi), "f"(lo)); return r;
}
__device__ __forceinline__ void stmatrix_x4(uint32_t addr, uint32_t a, uint32_t b, uint32_t c, uint32_t d) {
  asm volatile("stmatrix.sync.aligned.m8n8.x4.shared.b16 [%0], {%1,%2,%3,%4};" ::"r"(addr), "r"(a), "r"(b), "r"(c), "r"(d) : "memory");
}
__device__ __forceinline__ uint64_t policy_evict_first() {
  uint64_t p; asm("createpolicy.fractional.L2::evict_first.b64 %0, 1.0;" : "=l"(p)); return p;
}
__device__ __forceinline__ int4 ldg_stream(const int* p, uint64_t pol) {
  int4 v;
  asm volatile("ld.global.nc.L1::no_allocate.L2::cache_hint.v4.s32 {%0,%1,%2,%3}, [%4], %5;"
               : "=r"(v.x), "=r"(v.y), "=r"(v.z), "=r"(v.w) : "l"(p), "l"(pol));
  return v;
}
__device__ __forceinline__ void prefetch_l2(const void* p) { asm volatile("prefetch.global.L2 [%0];" ::"l"(p) : "memory"); }
__device__ __forceinline__ void wait_clock(uint32_t t0, int d) { while ((int)((uint32_t)clock() - t0) < d) {} }
__device__ __forceinline__ uint2 lds64(uint32_t a) {
  uint2 r; asm volatile("ld.shared.v2.u32 {%0,%1}, [%2];" : "=r"(r.x), "=r"(r.y) : "r"(a) : "memory"); return r;
}
__device__ __forceinline__ uint4 lds128(uint32_t a) {
  uint4 r; asm volatile("ld.shared.v4.u32 {%0,%1,%2,%3}, [%4];" : "=r"(r.x), "=r"(r.y), "=r"(r.z), "=r"(r.w) : "r"(a) : "memory"); return r;
}

struct Lut { uint32_t lo[4], hi[4]; };
__device__ __forceinline__ uint32_t prmt(uint32_t a, uint32_t b, uint32_t s) {
  uint32_t r; asm("prmt.b32 %0, %1, %2, %3;" : "=r"(r) : "r"(a), "r"(b), "r"(s)); return r;
}
__device__ __forceinline__ Lut make_lut(uint4 c0, uint4 c1) {
  Lut l;
  l.lo[0] = prmt(c0.x, c0.y, 0x6420); l.hi[0] = prmt(c0.x, c0.y, 0x7531);
  l.lo[1] = prmt(c0.z, c0.w, 0x6420); l.hi[1] = prmt(c0.z, c0.w, 0x7531);
  l.lo[2] = prmt(c1.x, c1.y, 0x6420); l.hi[2] = prmt(c1.x, c1.y, 0x7531);
  l.lo[3] = prmt(c1.z, c1.w, 0x6420); l.hi[3] = prmt(c1.z, c1.w, 0x7531);
  return l;
}
__device__ __forceinline__ uint2 dequant4(int4 v, const Lut& l, uint2 s) {
  const uint32_t sel = (uint32_t)(v.x + v.y * 16) + (uint32_t)(v.z + v.w * 16) * 256;
  const uint32_t s7 = sel & 0x7777, s2 = ((sel >> 1) & 0x4444) | 0x3210;
  const uint32_t lo = prmt(prmt(l.lo[0], l.lo[1], s7), prmt(l.lo[2], l.lo[3], s7), s2);
  const uint32_t hi = prmt(prmt(l.hi[0], l.hi[1], s7), prmt(l.hi[2], l.hi[3], s7), s2);
  uint2 r;
  asm("mul.rn.bf16x2 %0, %1, %2;" : "=r"(r.x) : "r"(prmt(lo, hi, 0x5140)), "r"(s.x));
  asm("mul.rn.bf16x2 %0, %1, %2;" : "=r"(r.y) : "r"(prmt(lo, hi, 0x7362)), "r"(s.y));
  return r;
}

template <int B0, int B1>
__device__ __forceinline__ void stage_boxes(const uint32_t (&pk)[56], uint32_t buf, int warp, int lane) {
  const int r = warp * 16 + (lane & 15), ch = lane >> 4;
#pragma unroll
  for (int b = B0; b < B1; b++) {
#pragma unroll
    for (int p = 0; p < 2; p++) {
      const int cc = p * 2 + ch;
      stmatrix_x4(buf + (b - B0) * 4096 + r * 64 + ((cc ^ ((r >> 1) & 3)) << 4),
                  pk[b * 8 + p * 4], pk[b * 8 + p * 4 + 1], pk[b * 8 + p * 4 + 2], pk[b * 8 + p * 4 + 3]);
    }
  }
}

__global__ void __cluster_dims__(2, 1, 1) __launch_bounds__(384, 1)
nf4_gemm_kernel(const int* __restrict__ q, const __nv_bfloat16* __restrict__ cb, const __nv_bfloat16* __restrict__ am,
                unsigned char* __restrict__ gw, const __nv_bfloat16* __restrict__ x,
                const __grid_constant__ CUtensorMap mx, const __grid_constant__ CUtensorMap mo) {
  extern __shared__ __align__(1024) unsigned char smem_raw[];
  const uint32_t sb = smem_u32(smem_raw);
  const uint32_t epi = sb + STAGES * STB, ring = epi + EPI, bars = ring + 4 * SLOTB;
  const uint32_t cst = bars + 512, cfull = bars + 192;
  auto full = [&](int s) { return bars + s * 8; };
  auto empty = [&](int s) { return bars + 32 + s * 8; };
  auto jdone = [&](int j) { return bars + 64 + j * 8; };
  unsigned int* gflag = (unsigned int*)(gw + (size_t)K * N * 2);
  unsigned int* gepoch = gflag + 256;

  const int c = blockIdx.x, wid = threadIdx.x >> 5, wg = wid >> 2, lane = threadIdx.x & 31, rank = c & 1;
  const int jc = c >> 1, b7 = jc - 36, k7 = (b7 * 37) >> 8;
  const int gidx = jc < 4 ? 15 : jc < 36 ? ((jc - 4) & 7) : 8 + b7 - 7 * k7;
  const int kidx = jc < 4 ? jc : jc < 36 ? ((jc - 4) >> 3) : k7;
  const int mt = (gidx & 7) * 2 + rank, pj = 4 * (gidx >> 3) + kidx;
  const uint32_t cstart = clock();

  const int grp = mt & 3, r0 = (mt >> 2) * 16 + (lane >> 3);
  auto img_off = [&](int r) {
    const int rr = r & 7;
    return (r >> 3) * 3584 + rr * 64 + ((((lane & 7) >> 1) ^ ((rr >> 1) & 3)) << 4) + (lane & 1) * 8;
  };

  const int* p0 = q + (size_t)(grp * 64 + r0) * N + pj * BN + wid * 32 + (lane & 7) * 4;
  int4 v[4]; uint4 cb0, cb1; uint2 sc0;
  asm volatile("{\n.reg .pred p;\nsetp.lt.s32 p, %12, 7;\n"
               "@p ld.global.nc.v4.u32 {%0,%1,%2,%3}, [%10];\n@p ld.global.nc.v4.u32 {%4,%5,%6,%7}, [%10+16];\n"
               "@p ld.global.nc.v2.u32 {%8,%9}, [%11];\n}"
               : "=r"(cb0.x), "=r"(cb0.y), "=r"(cb0.z), "=r"(cb0.w), "=r"(cb1.x), "=r"(cb1.y), "=r"(cb1.z), "=r"(cb1.w),
                 "=r"(sc0.x), "=r"(sc0.y)
               : "l"(cb), "l"(am + pj * BN + wid * 32 + (lane & 7) * 4), "r"(wid));
  {
    const uint64_t pol = policy_evict_first();
#pragma unroll
    for (int g = 0; g < 4; g++)
      asm volatile("{\n.reg .pred p;\nsetp.lt.s32 p, %6, 7;\n"
                   "@p ld.global.nc.L1::no_allocate.L2::cache_hint.v4.s32 {%0,%1,%2,%3}, [%4], %5;\n}"
                   : "=r"(v[g].x), "=r"(v[g].y), "=r"(v[g].z), "=r"(v[g].w)
                   : "l"(p0 + (size_t)g * 4 * N), "l"(pol), "r"(wid));
  }
  if (threadIdx.x == 288) {
    mbar_init(cfull, 1);
    fence_async_smem();
  } else if (threadIdx.x == 256) {
#pragma unroll
    for (int s = 0; s < STAGES; s++) { mbar_init(full(s), 1); mbar_init(empty(s), 4); }
    asm volatile("fence.mbarrier_init.release.cluster;" ::: "memory");
    fence_async_smem();
  } else if (threadIdx.x == 320) {
#pragma unroll
    for (int j = 0; j < 8; j++) mbar_init(jdone(j), j < 2 ? 7 : 2);
  }
  __syncthreads();
  cluster_arrive();

  if (wg == 2) {
    const int w = wid & 3;
    reg_dec<REG_SIDE>();
    if (w >= 2) {
      const __nv_bfloat16* xq = x + (size_t)(mt * BM + pj * 16 + (lane & 15)) * K;
      for (int i = w - 2; i < 4; i += 2) { wait_clock(cstart, T_XPF0 + i * T_XPF); if (lane < 16) prefetch_l2(xq + i * BK); }
      const uint64_t pol = policy_evict_first();
      const uint32_t myring = ring + (w - 2) * 2 * SLOTB + lane * 16;
      mbar_wait(cfull, 0);
      const Lut lut = make_lut(lds128(cst), lds128(cst + 16));
      uint2 sc[7];
#pragma unroll
      for (int g = 0; g < 7; g++) sc[g] = lds64(cst + 32 + g * 64 + (lane & 7) * 8);
      const int rw = r0 + (w - 2) * 8;
#pragma unroll 1
      for (int j = 2; j < 8; j++) {
        const int i = 4 * j + grp;
        wait_clock(cstart, T_JOB2 + (i - 8) * T_BLOCK);
        const int* p = q + (size_t)((i & 15) * 64 + rw) * N + (pj + (i >> 4) * 8) * BN + (lane & 7) * 4;
#pragma unroll
        for (int h = 0; h < 2; h++) {
#pragma unroll
          for (int g = 0; g < 7; g++)
            asm volatile("cp.async.cg.shared.global.L2::cache_hint [%0], [%1], 16, %2;"
                         ::"r"(myring + h * SLOTB + g * 512), "l"(p + (size_t)h * 4 * N + g * 32), "l"(pol) : "memory");
          asm volatile("cp.async.commit_group;" ::: "memory");
        }
        if (j == 4) {
#pragma unroll
          for (int g = 0; g < 7; g++) sc[g] = lds64(cst + 480 + g * 64 + (lane & 7) * 8);
        }
        unsigned char* blk = gw + ((size_t)(pj + (i >> 4) * 8) * KB + (i & 15)) * WB;
#pragma unroll 1
        for (int h = 0; h < 2; h++) {
          if (h == 0) asm volatile("cp.async.wait_group 1;" ::: "memory"); else asm volatile("cp.async.wait_group 0;" ::: "memory");
          uint4 u[7];
#pragma unroll
          for (int g = 0; g < 7; g++) u[g] = lds128(myring + h * SLOTB + g * 512);
          unsigned char* dst = blk + img_off(rw + h * 4);
#pragma unroll
          for (int g = 0; g < 7; g++)
            *(uint2*)(dst + g * 512) = dequant4(make_int4(u[g].x, u[g].y, u[g].z, u[g].w), lut, sc[g]);
        }
        __syncwarp();
        if (lane == 0) mbar_arrive(jdone(j));
      }
      cluster_wait();
    } else if (w == 1) {
      if (lane == 0) {
        mbar_expect_tx(cfull, 32 + 2 * 448);
        bulk_load(cst, cb, 32, cfull);
        bulk_load(cst + 32, am + pj * BN, 448, cfull);
        bulk_load(cst + 480, am + (pj + 8) * BN, 448, cfull);
      }
#pragma unroll 1
      for (int j = 0; j < 8; j++) {
        mbar_wait(jdone(j), 0);
        if (lane == 0) asm volatile("red.release.gpu.global.add.u32 [%0], 1;" ::"l"(gflag + pj * 32 + 4 * j + grp) : "memory");
        __syncwarp();
      }
      cluster_wait();
    } else {
      if (lane == 0) asm volatile("prefetch.tensormap [%0];" ::"l"(&mx) : "memory");
      const unsigned int epoch = gepoch[c];
      const unsigned int* fl = gflag + pj * 32 + lane;
      const __nv_bfloat16* xp = x + (size_t)(mt * BM + pj * 16 + (lane & 15)) * K;
      cluster_wait();
      const unsigned int target = (epoch + 1) * 4;
      unsigned int ready = 0;
      int s = 0, ph = 1;
      const unsigned char* wsrc = gw + (size_t)pj * KB * WB + rank * WH;
#pragma unroll 1
      for (int i = 0; i < NBLK; i++) {
        mbar_wait(empty(s), ph);
        const uint32_t xs = sb + s * STB, fb = full(s);
        if (i >= 4 && lane == 0) { mbar_expect_tx(fb, STB); tma_load_2d(xs, &mx, (i & 15) * BK, mt * BM, fb); }
        if (!((ready >> i) & 1)) {
          int spins = 0;
          do {
            unsigned int f;
            asm volatile("ld.relaxed.gpu.global.u32 %0, [%1];" : "=r"(f) : "l"(fl) : "memory");
            ready = __ballot_sync(~0u, (int)(f - target) >= 0);
            if (++spins > (1 << 22)) asm volatile("trap;");
          } while (!((ready >> i) & 1));
          asm volatile("fence.acquire.gpu;" ::: "memory");
          __syncwarp();
          if (lane == 0) asm volatile("fence.proxy.async.global;" ::: "memory");
        }
        if (lane == 0) {
          if (i < 4) mbar_expect_tx(fb, STB);
          bulk_load_multicast(xs + XB + rank * WH, wsrc, WH, fb, 3);
          if (i < 4) tma_load_2d(xs, &mx, (i & 15) * BK, mt * BM, fb);
        }
        if (i + 4 < KB && lane < 16) prefetch_l2(xp + (i + 4) * BK);
        wsrc += (i == KB - 1) ? (size_t)(7 * KB + 1) * WB : (size_t)WB;
        if (++s == STAGES) { s = 0; ph ^= 1; }
      }
      if (lane == 0) gepoch[c] = epoch + 1;
    }
  } else {
    const int warp = wid & 3;
    if (wid < 7) {
      const uint64_t pol = policy_evict_first();
      const Lut lut = make_lut(cb0, cb1);
      unsigned char* blk = gw + ((size_t)pj * KB + grp) * WB + wid * 512;
#pragma unroll 1
      for (int j = 0; j < 2; j++) {
#pragma unroll
        for (int g = 0; g < 4; g++) *(uint2*)(blk + img_off(r0 + g * 4)) = dequant4(v[g], lut, sc0);
        __syncwarp();
        if (lane == 0) mbar_arrive(jdone(j));
        if (j == 1) break;
        mbar_wait(jdone(0), 0);
        wait_clock(clock(), T_JOB1_DELAY);
#pragma unroll
        for (int g = 0; g < 4; g++) v[g] = ldg_stream(p0 + (size_t)(256 + g * 4) * N, pol);
        blk += 4 * WB;
      }
    }
    reg_inc<REG_CONSUMER>();
    const bool leader = (threadIdx.x & 127) == 0;
    if (leader) asm volatile("prefetch.tensormap [%0];" ::"l"(&mo) : "memory");
    float acc[112];
    const uint32_t empty_peer = mapa(empty(0), rank ^ 1);
    cluster_wait();
    int s = 0, ph = 0;
    auto mma_block = [&](int st, int first) {
      const uint64_t da = make_desc(sb + st * STB + wg * 8192, 16, 1024, 1), db = make_desc(sb + st * STB + XB, 512, 3584, 2);
      wg_fence();
#pragma unroll
      for (int k = 0; k < 4; k++) wgmma_n224<0>(acc, da + k * 2, db + k * 448, !(first && k == 0));
      wg_commit();
    };
    auto release_prev = [&]() {
      const int st = s == 0 ? STAGES - 1 : s - 1;
      if (leader) { mbar_arrive(empty(st)); mbar_arrive_remote(empty_peer + st * 8); }
    };
    auto advance = [&]() { if (++s == STAGES) { s = 0; ph ^= 1; } };

#pragma unroll 1
    for (int kb = 0; kb < KB; kb++) {
      mbar_wait(full(s), ph);
      mma_block(s, kb == 0);
      wg_wait<1>();
      if (kb > 0) release_prev();
      advance();
    }
    wg_wait<0>();
    release_prev();
    uint32_t pk[56];
#pragma unroll
    for (int i = 0; i < 56; i++) pk[i] = pack_bf16(acc[2 * i], acc[2 * i + 1]);

    const uint64_t opol = policy_evict_first();
    const uint32_t ebuf = epi + wg * 12288;
    const int row0 = mt * BM + wg * 64, col0 = pj * BN, col1 = (pj + 8) * BN;
#pragma unroll
    for (int kb = 0; kb < 7; kb++) {
      mbar_wait(full(s), ph);
      mma_block(s, kb == 0);
      if (kb > 0) { wg_wait<1>(); release_prev(); }
      advance();
      if (kb >= 3) { if (leader) bulk_wait_read<2>(); wg_sync(wg); }
      const uint32_t buf = ebuf + (kb % 3) * 4096;
      if (kb == 0) stage_boxes<0, 1>(pk, buf, warp, lane);
      if (kb == 1) stage_boxes<1, 2>(pk, buf, warp, lane);
      if (kb == 2) stage_boxes<2, 3>(pk, buf, warp, lane);
      if (kb == 3) stage_boxes<3, 4>(pk, buf, warp, lane);
      if (kb == 4) stage_boxes<4, 5>(pk, buf, warp, lane);
      if (kb == 5) stage_boxes<5, 6>(pk, buf, warp, lane);
      if (kb == 6) stage_boxes<6, 7>(pk, buf, warp, lane);
      fence_async_smem();
      wg_sync(wg);
      if (leader) { tma_store_2d(&mo, buf, col0 + kb * 32, row0, opol); bulk_commit(); }
    }
#pragma unroll 1
    for (int kb = 7; kb < KB; kb++) {
      mbar_wait(full(s), ph);
      mma_block(s, 0);
      wg_wait<1>();
      if (kb <= 12) release_prev();
      advance();
    }
    wg_wait<0>();
#pragma unroll
    for (int i = 0; i < 56; i++) pk[i] = pack_bf16(acc[2 * i], acc[2 * i + 1]);
    if (leader) bulk_wait_read<0>();
    wg_sync(wg);
    stage_boxes<0, 3>(pk, ebuf, warp, lane);
    fence_async_smem();
    wg_sync(wg);
    if (leader) {
      for (int b = 0; b < 3; b++) tma_store_2d(&mo, ebuf + b * 4096, col1 + b * 32, row0, opol);
      bulk_commit();
    }
    const uint32_t x0 = sb + wg * 8192, x1 = sb + STB + wg * 8192;
    stage_boxes<3, 5>(pk, x0, warp, lane);
    stage_boxes<5, 7>(pk, x1, warp, lane);
    fence_async_smem();
    wg_sync(wg);
    if (leader) {
      tma_store_2d(&mo, x0, col1 + 96, row0, opol);
      tma_store_2d(&mo, x0 + 4096, col1 + 128, row0, opol);
      tma_store_2d(&mo, x1, col1 + 160, row0, opol);
      tma_store_2d(&mo, x1 + 4096, col1 + 192, row0, opol);
      bulk_commit();
      bulk_wait<0>();
    }
  }
}

typedef CUresult (*EncodeTiledFn)(CUtensorMap*, CUtensorMapDataType, cuuint32_t, void*, const cuuint64_t*, const cuuint64_t*,
                                  const cuuint32_t*, const cuuint32_t*, CUtensorMapInterleave, CUtensorMapSwizzle,
                                  CUtensorMapL2promotion, CUtensorMapFloatOOBfill);

void make_map_2d(EncodeTiledFn enc, CUtensorMap* m, void* base, uint64_t inner, uint64_t outer, uint32_t b0, uint32_t b1,
                 CUtensorMapSwizzle sw, CUtensorMapL2promotion prom) {
  cuuint64_t dims[2] = {inner, outer};
  cuuint64_t strides[1] = {inner * 2};
  cuuint32_t box[2] = {b0, b1};
  cuuint32_t es[2] = {1, 1};
  enc(m, CU_TENSOR_MAP_DATA_TYPE_BFLOAT16, 2, base, dims, strides, box, es, CU_TENSOR_MAP_INTERLEAVE_NONE, sw, prom,
      CU_TENSOR_MAP_FLOAT_OOB_FILL_NONE);
}

}

extern "C" void kernel_launch(void* const* d_in, const int* in_sizes, int n_in, void* d_out, int out_size) {
  (void)in_sizes; (void)n_in; (void)out_size;
  static EncodeTiledFn enc = nullptr;
  static void* scratch = nullptr;
  if (!enc) {
    void* f = nullptr;
    cudaDriverEntryPointQueryResult qr;
    cudaGetDriverEntryPoint("cuTensorMapEncodeTiled", &f, cudaEnableDefault, &qr);
    enc = (EncodeTiledFn)f;
    cudaFuncSetAttribute(nf4_gemm_kernel, cudaFuncAttributeMaxDynamicSharedMemorySize, SMEM);
    cudaGetSymbolAddress(&scratch, g_scratch);
  }
  CUtensorMap mx, mo;
  make_map_2d(enc, &mx, d_in[0], K, M, BK, BM, CU_TENSOR_MAP_SWIZZLE_128B, CU_TENSOR_MAP_L2_PROMOTION_L2_128B);
  make_map_2d(enc, &mo, d_out, N, M, 32, 64, CU_TENSOR_MAP_SWIZZLE_64B, CU_TENSOR_MAP_L2_PROMOTION_NONE);
  nf4_gemm_kernel<<<128, 384, SMEM, cudaStreamPerThread>>>(
      (const int*)d_in[1], (const __nv_bfloat16*)d_in[2], (const __nv_bfloat16*)d_in[3], (unsigned char*)scratch,
      (const __nv_bfloat16*)d_in[0], mx, mo);
}
```

```cpp
#include <cuda_runtime.h>
#include <cuda_bf16.h>
#include <cuda.h>
#include <stdint.h>

namespace {

constexpr int M = 2048, N = 3584, K = 1024;
constexpr int BM = 128, BN = 224, BK = 64, KB = K / BK, STAGES = 4, NBLK = 2 * KB;
constexpr int XB = BM * BK * 2, WB = BN * BK * 2, STB = XB + WB, WH = WB / 2;
constexpr int EPI = 24576, SLOTB = 3584;
constexpr int SMEM = STAGES * STB + EPI + 4 * SLOTB + 512 + 1024;
constexpr int REG_CONSUMER = 208, REG_SIDE = 88;
constexpr int T_XPF0 = 1000, T_XPF = 200, T_JOB1 = 3300, T_JOB1_STEP = 400, T_JOB2 = 5000, T_BLOCK = 800;
constexpr uint64_t EVICT_FIRST = 0x12F0000000000000ull;

struct alignas(128) TensorMaps { CUtensorMap x, out; };

__device__ __align__(1024) unsigned char g_scratch[(size_t)K * N * 2 + 2048];

template <int OFF>
__device__ __forceinline__ void wgmma_n224(float (&d)[112], uint64_t da, uint64_t db, int scale_d) {
  asm volatile("{\n.reg .pred p;\nsetp.ne.b32 p, %114, 0;\n"
      "wgmma.mma_async.sync.aligned.m64n224k16.f32.bf16.bf16 {"
      "%0, %1, %2, %3, %4, %5, %6, %7, %8, %9, %10, %11, %12, %13, %14, %15, "
      "%16, %17, %18, %19, %20, %21, %22, %23, %24, %25, %26, %27, %28, %29, %30, %31, "
      "%32, %33, %34, %35, %36, %37, %38, %39, %40, %41, %42, %43, %44, %45, %46, %47, "
      "%48, %49, %50, %51, %52, %53, %54, %55, %56, %57, %58, %59, %60, %61, %62, %63, "
      "%64, %65, %66, %67, %68, %69, %70, %71, %72, %73, %74, %75, %76, %77, %78, %79, "
      "%80, %81, %82, %83, %84, %85, %86, %87, %88, %89, %90, %91, %92, %93, %94, %95, "
      "%96, %97, %98, %99, %100, %101, %102, %103, %104, %105, %106, %107, %108, %109, %110, %111"
      "}, %112, %113, p, 1, 1, 0, 1;\n}\n"
      : "+f"(d[OFF+0]), "+f"(d[OFF+1]), "+f"(d[OFF+2]), "+f"(d[OFF+3]), "+f"(d[OFF+4]), "+f"(d[OFF+5]), "+f"(d[OFF+6]), "+f"(d[OFF+7]),
      "+f"(d[OFF+8]), "+f"(d[OFF+9]), "+f"(d[OFF+10]), "+f"(d[OFF+11]), "+f"(d[OFF+12]), "+f"(d[OFF+13]), "+f"(d[OFF+14]), "+f"(d[OFF+15]),
      "+f"(d[OFF+16]), "+f"(d[OFF+17]), "+f"(d[OFF+18]), "+f"(d[OFF+19]), "+f"(d[OFF+20]), "+f"(d[OFF+21]), "+f"(d[OFF+22]), "+f"(d[OFF+23]),
      "+f"(d[OFF+24]), "+f"(d[OFF+25]), "+f"(d[OFF+26]), "+f"(d[OFF+27]), "+f"(d[OFF+28]), "+f"(d[OFF+29]), "+f"(d[OFF+30]), "+f"(d[OFF+31]),
      "+f"(d[OFF+32]), "+f"(d[OFF+33]), "+f"(d[OFF+34]), "+f"(d[OFF+35]), "+f"(d[OFF+36]), "+f"(d[OFF+37]), "+f"(d[OFF+38]), "+f"(d[OFF+39]),
      "+f"(d[OFF+40]), "+f"(d[OFF+41]), "+f"(d[OFF+42]), "+f"(d[OFF+43]), "+f"(d[OFF+44]), "+f"(d[OFF+45]), "+f"(d[OFF+46]), "+f"(d[OFF+47]),
      "+f"(d[OFF+48]), "+f"(d[OFF+49]), "+f"(d[OFF+50]), "+f"(d[OFF+51]), "+f"(d[OFF+52]), "+f"(d[OFF+53]), "+f"(d[OFF+54]), "+f"(d[OFF+55]),
      "+f"(d[OFF+56]), "+f"(d[OFF+57]), "+f"(d[OFF+58]), "+f"(d[OFF+59]), "+f"(d[OFF+60]), "+f"(d[OFF+61]), "+f"(d[OFF+62]), "+f"(d[OFF+63]),
      "+f"(d[OFF+64]), "+f"(d[OFF+65]), "+f"(d[OFF+66]), "+f"(d[OFF+67]), "+f"(d[OFF+68]), "+f"(d[OFF+69]), "+f"(d[OFF+70]), "+f"(d[OFF+71]),
      "+f"(d[OFF+72]), "+f"(d[OFF+73]), "+f"(d[OFF+74]), "+f"(d[OFF+75]), "+f"(d[OFF+76]), "+f"(d[OFF+77]), "+f"(d[OFF+78]), "+f"(d[OFF+79]),
      "+f"(d[OFF+80]), "+f"(d[OFF+81]), "+f"(d[OFF+82]), "+f"(d[OFF+83]), "+f"(d[OFF+84]), "+f"(d[OFF+85]), "+f"(d[OFF+86]), "+f"(d[OFF+87]),
      "+f"(d[OFF+88]), "+f"(d[OFF+89]), "+f"(d[OFF+90]), "+f"(d[OFF+91]), "+f"(d[OFF+92]), "+f"(d[OFF+93]), "+f"(d[OFF+94]), "+f"(d[OFF+95]),
      "+f"(d[OFF+96]), "+f"(d[OFF+97]), "+f"(d[OFF+98]), "+f"(d[OFF+99]), "+f"(d[OFF+100]), "+f"(d[OFF+101]), "+f"(d[OFF+102]), "+f"(d[OFF+103]),
      "+f"(d[OFF+104]), "+f"(d[OFF+105]), "+f"(d[OFF+106]), "+f"(d[OFF+107]), "+f"(d[OFF+108]), "+f"(d[OFF+109]), "+f"(d[OFF+110]), "+f"(d[OFF+111])
      : "l"(da), "l"(db), "r"(scale_d));
}

__device__ __forceinline__ uint32_t smem_u32(const void* p) { return (uint32_t)__cvta_generic_to_shared(p); }
__device__ __forceinline__ void mbar_init(uint32_t bar, uint32_t cnt) {
  asm volatile("mbarrier.init.shared::cta.b64 [%0], %1;" ::"r"(bar), "r"(cnt) : "memory");
}
__device__ __forceinline__ void mbar_expect_tx(uint32_t bar, uint32_t bytes) {
  asm volatile("mbarrier.arrive.expect_tx.shared::cta.b64 _, [%0], %1;" ::"r"(bar), "r"(bytes) : "memory");
}
__device__ __forceinline__ void mbar_arrive(uint32_t bar) {
  asm volatile("mbarrier.arrive.shared::cta.b64 _, [%0];" ::"r"(bar) : "memory");
}
__device__ __forceinline__ void mbar_arrive_remote(uint32_t cluster_addr) {
  asm volatile("mbarrier.arrive.shared::cluster.b64 _, [%0];" ::"r"(cluster_addr) : "memory");
}
__device__ __forceinline__ void mbar_wait(uint32_t bar, uint32_t parity) {
  asm volatile(
      "{\n.reg .pred p;\n.reg .u32 n;\nmov.u32 n, 0;\n"
      "LAB_WAIT:\nmbarrier.try_wait.parity.shared::cta.b64 p, [%0], %1;\n@p bra LAB_DONE;\n"
      "add.u32 n, n, 1;\nsetp.lt.u32 p, n, 1048576;\n@p bra LAB_WAIT;\ntrap;\nLAB_DONE:\n}" ::"r"(bar), "r"(parity) : "memory");
}
__device__ __forceinline__ void bulk_load(uint32_t dst, const void* src, uint32_t bytes, uint32_t bar) {
  asm volatile("cp.async.bulk.shared::cluster.global.mbarrier::complete_tx::bytes [%0], [%1], %2, [%3];"
               ::"r"(dst), "l"(src), "r"(bytes), "r"(bar) : "memory");
}
__device__ __forceinline__ void tma_store_2d(const CUtensorMap* m, uint32_t src, int c0, int c1, uint64_t pol) {
  asm volatile("cp.async.bulk.tensor.2d.global.shared::cta.bulk_group.L2::cache_hint [%0, {%2, %3}], [%1], %4;"
               ::"l"(m), "r"(src), "r"(c0), "r"(c1), "l"(pol) : "memory");
}
__device__ __forceinline__ void bulk_commit() { asm volatile("cp.async.bulk.commit_group;" ::: "memory"); }
template <int NG> __device__ __forceinline__ void bulk_wait_read() { asm volatile("cp.async.bulk.wait_group.read %0;" ::"n"(NG) : "memory"); }
__device__ __forceinline__ void fence_async_smem() { asm volatile("fence.proxy.async.shared::cta;" ::: "memory"); }
__device__ __forceinline__ void wg_fence() { asm volatile("wgmma.fence.sync.aligned;" ::: "memory"); }
__device__ __forceinline__ void wg_commit() { asm volatile("wgmma.commit_group.sync.aligned;" ::: "memory"); }
template <int NG> __device__ __forceinline__ void wg_wait() { asm volatile("wgmma.wait_group.sync.aligned %0;" ::"n"(NG) : "memory"); }
__device__ __forceinline__ void cluster_arrive() { asm volatile("barrier.cluster.arrive.relaxed.aligned;" ::: "memory"); }
__device__ __forceinline__ void cluster_wait() { asm volatile("barrier.cluster.wait.aligned;" ::: "memory"); }
template <int R> __device__ __forceinline__ void reg_inc() { asm volatile("setmaxnreg.inc.sync.aligned.u32 %0;" ::"n"(R)); }
template <int R> __device__ __forceinline__ void reg_dec() { asm volatile("setmaxnreg.dec.sync.aligned.u32 %0;" ::"n"(R)); }
__device__ __forceinline__ void wg_sync(int wg) {
  if (wg == 0) asm volatile("bar.sync 1, 128;" ::: "memory"); else asm volatile("bar.sync 2, 128;" ::: "memory");
}
__device__ __forceinline__ uint32_t mapa(uint32_t a, uint32_t cta) {
  uint32_t r; asm("mapa.shared::cluster.u32 %0, %1, %2;" : "=r"(r) : "r"(a), "r"(cta)); return r;
}
__device__ __forceinline__ uint64_t make_desc(uint32_t addr, uint32_t lbo, uint32_t sbo, uint32_t mode) {
  return (uint64_t)((addr & 0x3FFFF) >> 4) | ((uint64_t)(lbo >> 4) << 16) | ((uint64_t)(sbo >> 4) << 32) | ((uint64_t)mode << 62);
}
__device__ __forceinline__ uint32_t pack_bf16(float lo, float hi) {
  uint32_t r; asm("cvt.rn.bf16x2.f32 %0, %1, %2;" : "=r"(r) : "f"(hi), "f"(lo)); return r;
}
__device__ __forceinline__ void stmatrix_x4(uint32_t addr, uint32_t a, uint32_t b, uint32_t c, uint32_t d) {
  asm volatile("stmatrix.sync.aligned.m8n8.x4.shared.b16 [%0], {%1,%2,%3,%4};" ::"r"(addr), "r"(a), "r"(b), "r"(c), "r"(d) : "memory");
}
__device__ __forceinline__ void prefetch_l2(const void* p) { asm volatile("prefetch.global.L2 [%0];" ::"l"(p) : "memory"); }
__device__ __forceinline__ void wait_clock(uint32_t t0, int d) { while ((int)((uint32_t)clock() - t0) < d) {} }
__device__ __forceinline__ uint2 lds64(uint32_t a) {
  uint2 r; asm volatile("ld.shared.v2.u32 {%0,%1}, [%2];" : "=r"(r.x), "=r"(r.y) : "r"(a) : "memory"); return r;
}
__device__ __forceinline__ uint4 lds128(uint32_t a) {
  uint4 r; asm volatile("ld.shared.v4.u32 {%0,%1,%2,%3}, [%4];" : "=r"(r.x), "=r"(r.y), "=r"(r.z), "=r"(r.w) : "r"(a) : "memory"); return r;
}

template <bool ARM, bool X, bool W>
__device__ __forceinline__ void issue_stage(uint32_t bar, uint32_t xdst, const CUtensorMap* m, int c0, int c1,
                                            uint32_t wdst, const void* wsrc) {
  asm volatile("{\n.reg .pred p, px, pw, pa;\nelect.sync _|p, 0xffffffff;\n"
               "setp.ne.and.u32 pa, %7, 0, p;\nsetp.ne.and.u32 px, %8, 0, p;\nsetp.ne.and.u32 pw, %9, 0, p;\n"
               "@pa mbarrier.arrive.expect_tx.shared::cta.b64 _, [%0], %10;\n"
               "@pw cp.async.bulk.shared::cluster.global.mbarrier::complete_tx::bytes.multicast::cluster [%5], [%6], %11, [%0], %12;\n"
               "@px cp.async.bulk.tensor.2d.shared::cluster.global.mbarrier::complete_tx::bytes [%1], [%2, {%3, %4}], [%0];\n}"
               ::"r"(bar), "r"(xdst), "l"(m), "r"(c0), "r"(c1), "r"(wdst), "l"(wsrc), "n"((int)ARM), "n"((int)X), "n"((int)W),
                 "n"(STB), "n"(WH), "h"((uint16_t)3) : "memory");
}

struct Lut { uint32_t lo[4], hi[4]; };
__device__ __forceinline__ uint32_t prmt(uint32_t a, uint32_t b, uint32_t s) {
  uint32_t r; asm("prmt.b32 %0, %1, %2, %3;" : "=r"(r) : "r"(a), "r"(b), "r"(s)); return r;
}
__device__ __forceinline__ Lut make_lut(uint4 c0, uint4 c1) {
  Lut l;
  l.lo[0] = prmt(c0.x, c0.y, 0x6420); l.hi[0] = prmt(c0.x, c0.y, 0x7531);
  l.lo[1] = prmt(c0.z, c0.w, 0x6420); l.hi[1] = prmt(c0.z, c0.w, 0x7531);
  l.lo[2] = prmt(c1.x, c1.y, 0x6420); l.hi[2] = prmt(c1.x, c1.y, 0x7531);
  l.lo[3] = prmt(c1.z, c1.w, 0x6420); l.hi[3] = prmt(c1.z, c1.w, 0x7531);
  return l;
}
__device__ __forceinline__ uint2 dequant4(int4 v, const Lut& l, uint2 s) {
  const uint32_t sel = (uint32_t)(v.x + v.y * 16) + (uint32_t)(v.z + v.w * 16) * 256;
  const uint32_t s7 = sel & 0x7777, s2 = ((sel >> 1) & 0x4444) | 0x3210;
  const uint32_t lo = prmt(prmt(l.lo[0], l.lo[1], s7), prmt(l.lo[2], l.lo[3], s7), s2);
  const uint32_t hi = prmt(prmt(l.hi[0], l.hi[1], s7), prmt(l.hi[2], l.hi[3], s7), s2);
  uint2 r;
  asm("mul.rn.bf16x2 %0, %1, %2;" : "=r"(r.x) : "r"(prmt(lo, hi, 0x5140)), "r"(s.x));
  asm("mul.rn.bf16x2 %0, %1, %2;" : "=r"(r.y) : "r"(prmt(lo, hi, 0x7362)), "r"(s.y));
  return r;
}

template <int B0, int B1>
__device__ __forceinline__ void stage_boxes(const uint32_t (&pk)[56], uint32_t buf, int warp, int lane) {
  const int r = warp * 16 + (lane & 15), ch = lane >> 4;
#pragma unroll
  for (int b = B0; b < B1; b++) {
#pragma unroll
    for (int p = 0; p < 2; p++) {
      const int cc = p * 2 + ch;
      stmatrix_x4(buf + (b - B0) * 4096 + r * 64 + ((cc ^ ((r >> 1) & 3)) << 4),
                  pk[b * 8 + p * 4], pk[b * 8 + p * 4 + 1], pk[b * 8 + p * 4 + 2], pk[b * 8 + p * 4 + 3]);
    }
  }
}

__global__ void __cluster_dims__(2, 1, 1) __launch_bounds__(384, 1)
nf4_gemm_kernel(const int* __restrict__ q, const __nv_bfloat16* __restrict__ cb, const __nv_bfloat16* __restrict__ am,
                unsigned char* __restrict__ gw, const __nv_bfloat16* __restrict__ x,
                const __grid_constant__ TensorMaps maps) {
  const CUtensorMap& mx = maps.x;
  const CUtensorMap& mo = maps.out;
  extern __shared__ __align__(1024) unsigned char smem_raw[];
  const uint32_t sb = smem_u32(smem_raw);
  const uint32_t epi = sb + STAGES * STB, ring = epi + EPI, bars = ring + 4 * SLOTB;
  const uint32_t cst = bars + 512, cfull = bars + 192;
  auto full = [&](int s) { return bars + s * 8; };
  auto empty = [&](int s) { return bars + 32 + s * 8; };
  auto jdone = [&](int j) { return bars + 64 + j * 8; };
  unsigned int* gflag = (unsigned int*)(gw + (size_t)K * N * 2);
  unsigned int* gepoch = gflag + 256;

  const int c = blockIdx.x, wid = threadIdx.x >> 5, wg = wid >> 2, lane = threadIdx.x & 31, rank = c & 1;
  const int jc = c >> 1, b7 = jc - 36, k7 = (b7 * 37) >> 8;
  const int gidx = jc < 4 ? 15 : jc < 36 ? ((jc - 4) & 7) : 8 + b7 - 7 * k7;
  const int kidx = jc < 4 ? jc : jc < 36 ? ((jc - 4) >> 3) : k7;
  const int mt = (gidx & 7) * 2 + rank, pj = 4 * (gidx >> 3) + kidx;

  const int grp = mt & 3, r0 = (mt >> 2) * 16 + (lane >> 3);
  const int col = pj * BN + wid * 32 + (lane & 7) * 4;
  int4 v[4]; uint4 cb0, cb1; uint2 sc0;
  asm volatile("{\n.reg .pred p;\nsetp.lt.s32 p, %30, 7;\n"
               "@p ld.global.nc.v4.u32 {%16,%17,%18,%19}, [%27];\n@p ld.global.nc.v4.u32 {%20,%21,%22,%23}, [%27+16];\n"
               "@p ld.global.nc.v2.u32 {%24,%25}, [%28];\n"
               "@p ld.global.nc.L1::no_allocate.L2::cache_hint.v4.s32 {%0,%1,%2,%3}, [%26], %29;\n"
               "@p ld.global.nc.L1::no_allocate.L2::cache_hint.v4.s32 {%4,%5,%6,%7}, [%26+57344], %29;\n"
               "@p ld.global.nc.L1::no_allocate.L2::cache_hint.v4.s32 {%8,%9,%10,%11}, [%26+114688], %29;\n"
               "@p ld.global.nc.L1::no_allocate.L2::cache_hint.v4.s32 {%12,%13,%14,%15}, [%26+172032], %29;\n}"
               : "=r"(v[0].x), "=r"(v[0].y), "=r"(v[0].z), "=r"(v[0].w), "=r"(v[1].x), "=r"(v[1].y), "=r"(v[1].z), "=r"(v[1].w),
                 "=r"(v[2].x), "=r"(v[2].y), "=r"(v[2].z), "=r"(v[2].w), "=r"(v[3].x), "=r"(v[3].y), "=r"(v[3].z), "=r"(v[3].w),
                 "=r"(cb0.x), "=r"(cb0.y), "=r"(cb0.z), "=r"(cb0.w), "=r"(cb1.x), "=r"(cb1.y), "=r"(cb1.z), "=r"(cb1.w),
                 "=r"(sc0.x), "=r"(sc0.y)
               : "l"(q + (grp * 64 + r0) * N + col), "l"(cb), "l"(am + col), "l"(EVICT_FIRST), "r"(wid));
  const uint32_t cstart = clock();
  auto img_off = [&](int r) {
    const int rr = r & 7;
    return (r >> 3) * 3584 + rr * 64 + ((((lane & 7) >> 1) ^ ((rr >> 1) & 3)) << 4) + (lane & 1) * 8;
  };
  if (threadIdx.x == 288) {
    mbar_init(cfull, 1);
    fence_async_smem();
  } else if (threadIdx.x == 256) {
#pragma unroll
    for (int s = 0; s < STAGES; s++) { mbar_init(full(s), 1); mbar_init(empty(s), 4); }
    asm volatile("fence.mbarrier_init.release.cluster;" ::: "memory");
    fence_async_smem();
  } else if (threadIdx.x == 320) {
#pragma unroll
    for (int j = 0; j < 8; j++) mbar_init(jdone(j), j == 0 ? 7 : 2);
  }
  __syncthreads();
  cluster_arrive();

  if (wg == 2) {
    const int w = wid & 3;
    if (w >= 2) {
      reg_dec<REG_SIDE>();
      const __nv_bfloat16* xq = x + (size_t)(mt * BM + pj * 16 + (lane & 15)) * K;
      for (int i = w - 2; i < 4; i += 2) { wait_clock(cstart, T_XPF0 + i * T_XPF); if (lane < 16) prefetch_l2(xq + i * BK); }
      const uint32_t myring = ring + (w - 2) * 2 * SLOTB + lane * 16;
      mbar_wait(cfull, 0);
      const Lut lut = make_lut(lds128(cst), lds128(cst + 16));
      uint2 sc[7];
#pragma unroll
      for (int g = 0; g < 7; g++) sc[g] = lds64(cst + 32 + g * 64 + (lane & 7) * 8);
      const int rw = r0 + (w - 2) * 8;
#pragma unroll 1
      for (int j = 1; j < 8; j++) {
        const int i = 4 * j + grp;
        wait_clock(cstart, j == 1 ? T_JOB1 + grp * T_JOB1_STEP : T_JOB2 + (i - 8) * T_BLOCK);
        const int* p = q + (size_t)((i & 15) * 64 + rw) * N + (pj + (i >> 4) * 8) * BN + (lane & 7) * 4;
#pragma unroll
        for (int h = 0; h < 2; h++) {
#pragma unroll
          for (int g = 0; g < 7; g++)
            asm volatile("cp.async.cg.shared.global.L2::cache_hint [%0], [%1], 16, %2;"
                         ::"r"(myring + h * SLOTB + g * 512), "l"(p + (size_t)h * 4 * N + g * 32), "l"(EVICT_FIRST) : "memory");
          asm volatile("cp.async.commit_group;" ::: "memory");
        }
        if (j == 4) {
#pragma unroll
          for (int g = 0; g < 7; g++) sc[g] = lds64(cst + 480 + g * 64 + (lane & 7) * 8);
        }
        unsigned char* blk = gw + ((size_t)(pj + (i >> 4) * 8) * KB + (i & 15)) * WB;
#pragma unroll 1
        for (int h = 0; h < 2; h++) {
          if (h == 0) asm volatile("cp.async.wait_group 1;" ::: "memory"); else asm volatile("cp.async.wait_group 0;" ::: "memory");
          uint4 u[7];
#pragma unroll
          for (int g = 0; g < 7; g++) u[g] = lds128(myring + h * SLOTB + g * 512);
          unsigned char* dst = blk + img_off(rw + h * 4);
#pragma unroll
          for (int g = 0; g < 7; g++)
            *(uint2*)(dst + g * 512) = dequant4(make_int4(u[g].x, u[g].y, u[g].z, u[g].w), lut, sc[g]);
        }
        __syncwarp();
        if (lane == 0) mbar_arrive(jdone(j));
      }
      cluster_wait();
    } else if (w == 1) {
      reg_dec<REG_SIDE>();
      if (lane == 0) {
        mbar_expect_tx(cfull, 32 + 2 * 448);
        bulk_load(cst, cb, 32, cfull);
        bulk_load(cst + 32, am + pj * BN, 448, cfull);
        bulk_load(cst + 480, am + (pj + 8) * BN, 448, cfull);
      }
#pragma unroll 1
      for (int j = 0; j < 8; j++) {
        mbar_wait(jdone(j), 0);
        if (lane == 0) asm volatile("red.release.gpu.global.add.u32 [%0], 1;" ::"l"(gflag + pj * 32 + 4 * j + grp) : "memory");
        __syncwarp();
      }
      cluster_wait();
    } else {
      reg_dec<REG_SIDE>();
      if (lane == 0) asm volatile("prefetch.tensormap [%0];" ::"l"(&mx) : "memory");
      const unsigned int epoch = gepoch[c];
      const unsigned int* fl = gflag + pj * 32 + lane;
      const __nv_bfloat16* xp = x + (size_t)(mt * BM + pj * 16 + (lane & 15)) * K;
      cluster_wait();
      const unsigned int target = (epoch + 1) * 4;
      unsigned int ready = 0;
      int s = 0, ph = 1;
      const unsigned char* wsrc = gw + (size_t)pj * KB * WB + rank * WH;
#pragma unroll 1
      for (int i = 0; i < NBLK; i++) {
        const uint32_t xs = sb + s * STB, ws = xs + XB + rank * WH, fb = full(s);
        const int kc = (i & 15) * BK;
        if ((ready >> i) & 1) {
          if (i == 2 || i == 3) mbar_wait(full(i - 2), 0);
          mbar_wait(empty(s), ph);
          issue_stage<true, true, true>(fb, xs, &mx, kc, mt * BM, ws, wsrc);
        } else {
          mbar_wait(empty(s), ph);
          if (i >= 4) issue_stage<true, true, false>(fb, xs, &mx, kc, mt * BM, ws, wsrc);
          int spins = 0;
          do {
            unsigned int f;
            asm volatile("ld.relaxed.gpu.global.u32 %0, [%1];" : "=r"(f) : "l"(fl) : "memory");
            ready = __ballot_sync(~0u, (int)(f - target) >= 0);
            if (++spins > (1 << 22)) asm volatile("trap;");
          } while (!((ready >> i) & 1));
          asm volatile("fence.acquire.gpu;" ::: "memory");
          __syncwarp();
          asm volatile("fence.proxy.async.global;" ::: "memory");
          if (i >= 4) {
            issue_stage<false, false, true>(fb, xs, &mx, kc, mt * BM, ws, wsrc);
          } else {
            if (i >= 2) mbar_wait(full(i - 2), 0);
            issue_stage<true, true, true>(fb, xs, &mx, kc, mt * BM, ws, wsrc);
          }
        }
        if (i + 4 < KB && lane < 16) prefetch_l2(xp + (i + 4) * BK);
        wsrc += (i == KB - 1) ? (size_t)(7 * KB + 1) * WB : (size_t)WB;
        if (++s == STAGES) { s = 0; ph ^= 1; }
      }
      if (lane == 0) gepoch[c] = epoch + 1;
    }
  } else {
    const int warp = wid & 3;
    if (wid < 7) {
      const Lut lut = make_lut(cb0, cb1);
      unsigned char* blk = gw + ((size_t)pj * KB + grp) * WB + wid * 512;
#pragma unroll
      for (int g = 0; g < 4; g++) *(uint2*)(blk + img_off(r0 + g * 4)) = dequant4(v[g], lut, sc0);
      __syncwarp();
      if (lane == 0) mbar_arrive(jdone(0));
    }
    reg_inc<REG_CONSUMER>();
    const bool leader = (threadIdx.x & 127) == 0;
    if (leader) asm volatile("prefetch.tensormap [%0];" ::"l"(&mo) : "memory");
    float acc[112];
    const uint32_t empty_peer = mapa(empty(0), rank ^ 1);
    cluster_wait();
    int s = 0, ph = 0;
    auto mma_block = [&](int st, int first) {
      const uint64_t da = make_desc(sb + st * STB + wg * 8192, 16, 1024, 1), db = make_desc(sb + st * STB + XB, 512, 3584, 2);
      wg_fence();
#pragma unroll
      for (int k = 0; k < 4; k++) wgmma_n224<0>(acc, da + k * 2, db + k * 448, !(first && k == 0));
      wg_commit();
    };
    auto release_prev = [&]() {
      const int st = s == 0 ? STAGES - 1 : s - 1;
      if (leader) { mbar_arrive(empty(st)); mbar_arrive_remote(empty_peer + st * 8); }
    };
    auto advance = [&]() { if (++s == STAGES) { s = 0; ph ^= 1; } };

#pragma unroll 1
    for (int kb = 0; kb < KB; kb++) {
      mbar_wait(full(s), ph);
      mma_block(s, kb == 0);
      wg_wait<1>();
      if (kb > 0) release_prev();
      advance();
    }
    wg_wait<0>();
    release_prev();
    uint32_t pk[56];
#pragma unroll
    for (int i = 0; i < 56; i++) pk[i] = pack_bf16(acc[2 * i], acc[2 * i + 1]);

    const uint32_t ebuf = epi + wg * 12288;
    const int row0 = mt * BM + wg * 64, col0 = pj * BN, col1 = (pj + 8) * BN;
#pragma unroll
    for (int kb = 0; kb < 7; kb++) {
      mbar_wait(full(s), ph);
      mma_block(s, kb == 0);
      if (kb > 0) { wg_wait<1>(); release_prev(); }
      advance();
      if (kb >= 3) { if (leader) bulk_wait_read<2>(); wg_sync(wg); }
      const uint32_t buf = ebuf + (kb % 3) * 4096;
      if (kb == 0) stage_boxes<0, 1>(pk, buf, warp, lane);
      if (kb == 1) stage_boxes<1, 2>(pk, buf, warp, lane);
      if (kb == 2) stage_boxes<2, 3>(pk, buf, warp, lane);
      if (kb == 3) stage_boxes<3, 4>(pk, buf, warp, lane);
      if (kb == 4) stage_boxes<4, 5>(pk, buf, warp, lane);
      if (kb == 5) stage_boxes<5, 6>(pk, buf, warp, lane);
      if (kb == 6) stage_boxes<6, 7>(pk, buf, warp, lane);
      fence_async_smem();
      wg_sync(wg);
      if (leader) { tma_store_2d(&mo, buf, col0 + kb * 32, row0, EVICT_FIRST); bulk_commit(); }
    }
#pragma unroll 1
    for (int kb = 7; kb < KB; kb++) {
      const bool hold = kb == KB - 4 && wg == 1;
      if (hold) { wg_wait<0>(); release_prev(); asm volatile("bar.sync 4, 256;" ::: "memory"); }
      mbar_wait(full(s), ph);
      mma_block(s, 0);
      wg_wait<1>();
      if (kb <= KB - 4 && !hold) release_prev();
      if (kb == 10 && leader) bulk_wait_read<0>();
      if (kb == KB - 1 && wg == 0) asm volatile("bar.arrive 4, 256;" ::: "memory");
      advance();
    }
    wg_wait<0>();
    const uint32_t x0 = sb + wg * 8192, x1 = sb + STB + wg * 8192;
    auto box_buf = [&](int b) { return b < 3 ? ebuf + b * 4096 : b < 5 ? x0 + (b - 3) * 4096 : x1 + (b - 5) * 4096; };
#pragma unroll
    for (int b = 0; b < 7; b++) {
#pragma unroll
      for (int i = b * 8; i < b * 8 + 8; i++) pk[i] = pack_bf16(acc[2 * i], acc[2 * i + 1]);
      const int r = warp * 16 + (lane & 15), ch = lane >> 4;
#pragma unroll
      for (int p = 0; p < 2; p++)
        stmatrix_x4(box_buf(b) + r * 64 + (((p * 2 + ch) ^ ((r >> 1) & 3)) << 4),
                    pk[b * 8 + p * 4], pk[b * 8 + p * 4 + 1], pk[b * 8 + p * 4 + 2], pk[b * 8 + p * 4 + 3]);
      if (b == 1 || b == 3 || b == 6) {
        fence_async_smem();
        wg_sync(wg);
        const int b0 = b == 1 ? 0 : b == 3 ? 2 : 4;
        if (lane == 0 && warp <= b - b0) tma_store_2d(&mo, box_buf(b0 + warp), col1 + (b0 + warp) * 32, row0, EVICT_FIRST);
      }
    }
    if (lane == 0) { bulk_commit(); bulk_wait_read<0>(); }
  }
}

typedef CUresult (*EncodeTiledFn)(CUtensorMap*, CUtensorMapDataType, cuuint32_t, void*, const cuuint64_t*, const cuuint64_t*,
                                  const cuuint32_t*, const cuuint32_t*, CUtensorMapInterleave, CUtensorMapSwizzle,
                                  CUtensorMapL2promotion, CUtensorMapFloatOOBfill);

void make_map_2d(EncodeTiledFn enc, CUtensorMap* m, void* base, uint64_t inner, uint64_t outer, uint32_t b0, uint32_t b1,
                 CUtensorMapSwizzle sw, CUtensorMapL2promotion prom) {
  cuuint64_t dims[2] = {inner, outer};
  cuuint64_t strides[1] = {inner * 2};
  cuuint32_t box[2] = {b0, b1};
  cuuint32_t es[2] = {1, 1};
  enc(m, CU_TENSOR_MAP_DATA_TYPE_BFLOAT16, 2, base, dims, strides, box, es, CU_TENSOR_MAP_INTERLEAVE_NONE, sw, prom,
      CU_TENSOR_MAP_FLOAT_OOB_FILL_NONE);
}

}

extern "C" void kernel_launch(void* const* d_in, const int* in_sizes, int n_in, void* d_out, int out_size) {
  (void)in_sizes; (void)n_in; (void)out_size;
  static EncodeTiledFn enc = nullptr;
  static void* scratch = nullptr;
  if (!enc) {
    void* f = nullptr;
    cudaDriverEntryPointQueryResult qr;
    cudaGetDriverEntryPoint("cuTensorMapEncodeTiled", &f, cudaEnableDefault, &qr);
    enc = (EncodeTiledFn)f;
    cudaFuncSetAttribute(nf4_gemm_kernel, cudaFuncAttributeMaxDynamicSharedMemorySize, SMEM);
    cudaGetSymbolAddress(&scratch, g_scratch);
  }
  TensorMaps maps;
  make_map_2d(enc, &maps.x, d_in[0], K, M, BK, BM, CU_TENSOR_MAP_SWIZZLE_128B, CU_TENSOR_MAP_L2_PROMOTION_L2_128B);
  make_map_2d(enc, &maps.out, d_out, N, M, 32, 64, CU_TENSOR_MAP_SWIZZLE_64B, CU_TENSOR_MAP_L2_PROMOTION_NONE);
  nf4_gemm_kernel<<<128, 384, SMEM, cudaStreamPerThread>>>(
      (const int*)d_in[1], (const __nv_bfloat16*)d_in[2], (const __nv_bfloat16*)d_in[3], (unsigned char*)scratch,
      (const __nv_bfloat16*)d_in[0], maps);
}
```

```cpp
#include <cuda_runtime.h>
#include <cuda_bf16.h>
#include <cuda.h>
#include <stdint.h>

namespace {

constexpr int M = 2048, N = 3584, K = 1024;
constexpr int BM = 128, BN = 224, BK = 64, KB = K / BK, STAGES = 4, NBLK = 2 * KB;
constexpr int XB = BM * BK * 2, WB = BN * BK * 2, STB = XB + WB, WH = WB / 2;
constexpr int EPI = 24576, SLOTB = 3584;
constexpr int SMEM = STAGES * STB + EPI + 4 * SLOTB + 512 + 1024;
constexpr int REG_CONSUMER = 208, REG_SIDE = 88;
constexpr int T_JOB0_STEP = 300, T_XPF0 = 1400, T_XPF = 200, T_JOB1 = 3000, T_JOB1_STEP = 450, T_JOB2 = 5500, T_BLOCK = 750;
constexpr uint64_t EVICT_FIRST = 0x12F0000000000000ull;

struct alignas(128) TensorMaps { CUtensorMap x, out; };

__device__ __align__(1024) unsigned char g_scratch[(size_t)K * N * 2 + 2048];

template <int OFF>
__device__ __forceinline__ void wgmma_n224(float (&d)[112], uint64_t da, uint64_t db, int scale_d) {
  asm volatile("{\n.reg .pred p;\nsetp.ne.b32 p, %114, 0;\n"
      "wgmma.mma_async.sync.aligned.m64n224k16.f32.bf16.bf16 {"
      "%0, %1, %2, %3, %4, %5, %6, %7, %8, %9, %10, %11, %12, %13, %14, %15, "
      "%16, %17, %18, %19, %20, %21, %22, %23, %24, %25, %26, %27, %28, %29, %30, %31, "
      "%32, %33, %34, %35, %36, %37, %38, %39, %40, %41, %42, %43, %44, %45, %46, %47, "
      "%48, %49, %50, %51, %52, %53, %54, %55, %56, %57, %58, %59, %60, %61, %62, %63, "
      "%64, %65, %66, %67, %68, %69, %70, %71, %72, %73, %74, %75, %76, %77, %78, %79, "
      "%80, %81, %82, %83, %84, %85, %86, %87, %88, %89, %90, %91, %92, %93, %94, %95, "
      "%96, %97, %98, %99, %100, %101, %102, %103, %104, %105, %106, %107, %108, %109, %110, %111"
      "}, %112, %113, p, 1, 1, 0, 1;\n}\n"
      : "+f"(d[OFF+0]), "+f"(d[OFF+1]), "+f"(d[OFF+2]), "+f"(d[OFF+3]), "+f"(d[OFF+4]), "+f"(d[OFF+5]), "+f"(d[OFF+6]), "+f"(d[OFF+7]),
      "+f"(d[OFF+8]), "+f"(d[OFF+9]), "+f"(d[OFF+10]), "+f"(d[OFF+11]), "+f"(d[OFF+12]), "+f"(d[OFF+13]), "+f"(d[OFF+14]), "+f"(d[OFF+15]),
      "+f"(d[OFF+16]), "+f"(d[OFF+17]), "+f"(d[OFF+18]), "+f"(d[OFF+19]), "+f"(d[OFF+20]), "+f"(d[OFF+21]), "+f"(d[OFF+22]), "+f"(d[OFF+23]),
      "+f"(d[OFF+24]), "+f"(d[OFF+25]), "+f"(d[OFF+26]), "+f"(d[OFF+27]), "+f"(d[OFF+28]), "+f"(d[OFF+29]), "+f"(d[OFF+30]), "+f"(d[OFF+31]),
      "+f"(d[OFF+32]), "+f"(d[OFF+33]), "+f"(d[OFF+34]), "+f"(d[OFF+35]), "+f"(d[OFF+36]), "+f"(d[OFF+37]), "+f"(d[OFF+38]), "+f"(d[OFF+39]),
      "+f"(d[OFF+40]), "+f"(d[OFF+41]), "+f"(d[OFF+42]), "+f"(d[OFF+43]), "+f"(d[OFF+44]), "+f"(d[OFF+45]), "+f"(d[OFF+46]), "+f"(d[OFF+47]),
      "+f"(d[OFF+48]), "+f"(d[OFF+49]), "+f"(d[OFF+50]), "+f"(d[OFF+51]), "+f"(d[OFF+52]), "+f"(d[OFF+53]), "+f"(d[OFF+54]), "+f"(d[OFF+55]),
      "+f"(d[OFF+56]), "+f"(d[OFF+57]), "+f"(d[OFF+58]), "+f"(d[OFF+59]), "+f"(d[OFF+60]), "+f"(d[OFF+61]), "+f"(d[OFF+62]), "+f"(d[OFF+63]),
      "+f"(d[OFF+64]), "+f"(d[OFF+65]), "+f"(d[OFF+66]), "+f"(d[OFF+67]), "+f"(d[OFF+68]), "+f"(d[OFF+69]), "+f"(d[OFF+70]), "+f"(d[OFF+71]),
      "+f"(d[OFF+72]), "+f"(d[OFF+73]), "+f"(d[OFF+74]), "+f"(d[OFF+75]), "+f"(d[OFF+76]), "+f"(d[OFF+77]), "+f"(d[OFF+78]), "+f"(d[OFF+79]),
      "+f"(d[OFF+80]), "+f"(d[OFF+81]), "+f"(d[OFF+82]), "+f"(d[OFF+83]), "+f"(d[OFF+84]), "+f"(d[OFF+85]), "+f"(d[OFF+86]), "+f"(d[OFF+87]),
      "+f"(d[OFF+88]), "+f"(d[OFF+89]), "+f"(d[OFF+90]), "+f"(d[OFF+91]), "+f"(d[OFF+92]), "+f"(d[OFF+93]), "+f"(d[OFF+94]), "+f"(d[OFF+95]),
      "+f"(d[OFF+96]), "+f"(d[OFF+97]), "+f"(d[OFF+98]), "+f"(d[OFF+99]), "+f"(d[OFF+100]), "+f"(d[OFF+101]), "+f"(d[OFF+102]), "+f"(d[OFF+103]),
      "+f"(d[OFF+104]), "+f"(d[OFF+105]), "+f"(d[OFF+106]), "+f"(d[OFF+107]), "+f"(d[OFF+108]), "+f"(d[OFF+109]), "+f"(d[OFF+110]), "+f"(d[OFF+111])
      : "l"(da), "l"(db), "r"(scale_d));
}

__device__ __forceinline__ uint32_t smem_u32(const void* p) { return (uint32_t)__cvta_generic_to_shared(p); }
__device__ __forceinline__ void mbar_init(uint32_t bar, uint32_t cnt) {
  asm volatile("mbarrier.init.shared::cta.b64 [%0], %1;" ::"r"(bar), "r"(cnt) : "memory");
}
__device__ __forceinline__ void mbar_expect_tx(uint32_t bar, uint32_t bytes) {
  asm volatile("mbarrier.arrive.expect_tx.shared::cta.b64 _, [%0], %1;" ::"r"(bar), "r"(bytes) : "memory");
}
__device__ __forceinline__ void mbar_arrive(uint32_t bar) {
  asm volatile("mbarrier.arrive.shared::cta.b64 _, [%0];" ::"r"(bar) : "memory");
}
__device__ __forceinline__ void mbar_arrive_remote(uint32_t cluster_addr) {
  asm volatile("mbarrier.arrive.shared::cluster.b64 _, [%0];" ::"r"(cluster_addr) : "memory");
}
__device__ __forceinline__ bool mbar_test(uint32_t bar, uint32_t parity) {
  uint32_t ok;
  asm volatile("{\n.reg .pred p;\nmbarrier.test_wait.parity.shared::cta.b64 p, [%1], %2;\nselp.u32 %0, 1, 0, p;\n}"
               : "=r"(ok) : "r"(bar), "r"(parity) : "memory");
  return ok;
}
__device__ __forceinline__ void mbar_wait(uint32_t bar, uint32_t parity) {
  asm volatile(
      "{\n.reg .pred p;\n.reg .u32 n;\nmov.u32 n, 0;\n"
      "LAB_WAIT:\nmbarrier.try_wait.parity.shared::cta.b64 p, [%0], %1;\n@p bra LAB_DONE;\n"
      "add.u32 n, n, 1;\nsetp.lt.u32 p, n, 1048576;\n@p bra LAB_WAIT;\ntrap;\nLAB_DONE:\n}" ::"r"(bar), "r"(parity) : "memory");
}
__device__ __forceinline__ void bulk_load(uint32_t dst, const void* src, uint32_t bytes, uint32_t bar) {
  asm volatile("cp.async.bulk.shared::cluster.global.mbarrier::complete_tx::bytes [%0], [%1], %2, [%3];"
               ::"r"(dst), "l"(src), "r"(bytes), "r"(bar) : "memory");
}
__device__ __forceinline__ void tma_store_2d(const CUtensorMap* m, uint32_t src, int c0, int c1, uint64_t pol) {
  asm volatile("cp.async.bulk.tensor.2d.global.shared::cta.bulk_group.L2::cache_hint [%0, {%2, %3}], [%1], %4;"
               ::"l"(m), "r"(src), "r"(c0), "r"(c1), "l"(pol) : "memory");
}
__device__ __forceinline__ void bulk_commit() { asm volatile("cp.async.bulk.commit_group;" ::: "memory"); }
template <int NG> __device__ __forceinline__ void bulk_wait_read() { asm volatile("cp.async.bulk.wait_group.read %0;" ::"n"(NG) : "memory"); }
__device__ __forceinline__ void fence_async_smem() { asm volatile("fence.proxy.async.shared::cta;" ::: "memory"); }
__device__ __forceinline__ void wg_fence() { asm volatile("wgmma.fence.sync.aligned;" ::: "memory"); }
__device__ __forceinline__ void wg_commit() { asm volatile("wgmma.commit_group.sync.aligned;" ::: "memory"); }
template <int NG> __device__ __forceinline__ void wg_wait() { asm volatile("wgmma.wait_group.sync.aligned %0;" ::"n"(NG) : "memory"); }
__device__ __forceinline__ void cluster_arrive() { asm volatile("barrier.cluster.arrive.relaxed.aligned;" ::: "memory"); }
__device__ __forceinline__ void cluster_wait() { asm volatile("barrier.cluster.wait.aligned;" ::: "memory"); }
template <int R> __device__ __forceinline__ void reg_inc() { asm volatile("setmaxnreg.inc.sync.aligned.u32 %0;" ::"n"(R)); }
template <int R> __device__ __forceinline__ void reg_dec() { asm volatile("setmaxnreg.dec.sync.aligned.u32 %0;" ::"n"(R)); }
__device__ __forceinline__ void wg_sync(int wg) {
  if (wg == 0) asm volatile("bar.sync 1, 128;" ::: "memory"); else asm volatile("bar.sync 2, 128;" ::: "memory");
}
__device__ __forceinline__ uint32_t mapa(uint32_t a, uint32_t cta) {
  uint32_t r; asm("mapa.shared::cluster.u32 %0, %1, %2;" : "=r"(r) : "r"(a), "r"(cta)); return r;
}
__device__ __forceinline__ uint64_t make_desc(uint32_t addr, uint32_t lbo, uint32_t sbo, uint32_t mode) {
  return (uint64_t)((addr & 0x3FFFF) >> 4) | ((uint64_t)(lbo >> 4) << 16) | ((uint64_t)(sbo >> 4) << 32) | ((uint64_t)mode << 62);
}
__device__ __forceinline__ uint32_t pack_bf16(float lo, float hi) {
  uint32_t r; asm("cvt.rn.bf16x2.f32 %0, %1, %2;" : "=r"(r) : "f"(hi), "f"(lo)); return r;
}
__device__ __forceinline__ void stmatrix_x4(uint32_t addr, uint32_t a, uint32_t b, uint32_t c, uint32_t d) {
  asm volatile("stmatrix.sync.aligned.m8n8.x4.shared.b16 [%0], {%1,%2,%3,%4};" ::"r"(addr), "r"(a), "r"(b), "r"(c), "r"(d) : "memory");
}
__device__ __forceinline__ void prefetch_l2(const void* p) { asm volatile("prefetch.global.L2 [%0];" ::"l"(p) : "memory"); }
__device__ __forceinline__ void wait_clock(uint32_t t0, int d) { while ((int)((uint32_t)clock() - t0) < d) {} }
__device__ __forceinline__ uint2 lds64(uint32_t a) {
  uint2 r; asm volatile("ld.shared.v2.u32 {%0,%1}, [%2];" : "=r"(r.x), "=r"(r.y) : "r"(a) : "memory"); return r;
}
__device__ __forceinline__ uint4 lds128(uint32_t a) {
  uint4 r; asm volatile("ld.shared.v4.u32 {%0,%1,%2,%3}, [%4];" : "=r"(r.x), "=r"(r.y), "=r"(r.z), "=r"(r.w) : "r"(a) : "memory"); return r;
}

template <bool ARM, bool X, bool W>
__device__ __forceinline__ void issue_stage(uint32_t bar, uint32_t xdst, const CUtensorMap* m, int c0, int c1,
                                            uint32_t wdst, const void* wsrc) {
  asm volatile("{\n.reg .pred p, px, pw, pa;\nelect.sync _|p, 0xffffffff;\n"
               "setp.ne.and.u32 pa, %7, 0, p;\nsetp.ne.and.u32 px, %8, 0, p;\nsetp.ne.and.u32 pw, %9, 0, p;\n"
               "@pa mbarrier.arrive.expect_tx.shared::cta.b64 _, [%0], %10;\n"
               "@pw cp.async.bulk.shared::cluster.global.mbarrier::complete_tx::bytes.multicast::cluster [%5], [%6], %11, [%0], %12;\n"
               "@px cp.async.bulk.tensor.2d.shared::cluster.global.mbarrier::complete_tx::bytes [%1], [%2, {%3, %4}], [%0];\n}"
               ::"r"(bar), "r"(xdst), "l"(m), "r"(c0), "r"(c1), "r"(wdst), "l"(wsrc), "n"((int)ARM), "n"((int)X), "n"((int)W),
                 "n"(STB), "n"(WH), "h"((uint16_t)3) : "memory");
}

struct Lut { uint32_t lo[4], hi[4]; };
__device__ __forceinline__ uint32_t prmt(uint32_t a, uint32_t b, uint32_t s) {
  uint32_t r; asm("prmt.b32 %0, %1, %2, %3;" : "=r"(r) : "r"(a), "r"(b), "r"(s)); return r;
}
__device__ __forceinline__ Lut make_lut(uint4 c0, uint4 c1) {
  Lut l;
  l.lo[0] = prmt(c0.x, c0.y, 0x6420); l.hi[0] = prmt(c0.x, c0.y, 0x7531);
  l.lo[1] = prmt(c0.z, c0.w, 0x6420); l.hi[1] = prmt(c0.z, c0.w, 0x7531);
  l.lo[2] = prmt(c1.x, c1.y, 0x6420); l.hi[2] = prmt(c1.x, c1.y, 0x7531);
  l.lo[3] = prmt(c1.z, c1.w, 0x6420); l.hi[3] = prmt(c1.z, c1.w, 0x7531);
  return l;
}
__device__ __forceinline__ uint2 dequant4(int4 v, const Lut& l, uint2 s) {
  const uint32_t sel = (uint32_t)(v.x + v.y * 16) + (uint32_t)(v.z + v.w * 16) * 256;
  const uint32_t s7 = sel & 0x7777, s2 = ((sel >> 1) & 0x4444) | 0x3210;
  const uint32_t lo = prmt(prmt(l.lo[0], l.lo[1], s7), prmt(l.lo[2], l.lo[3], s7), s2);
  const uint32_t hi = prmt(prmt(l.hi[0], l.hi[1], s7), prmt(l.hi[2], l.hi[3], s7), s2);
  uint2 r;
  asm("mul.rn.bf16x2 %0, %1, %2;" : "=r"(r.x) : "r"(prmt(lo, hi, 0x5140)), "r"(s.x));
  asm("mul.rn.bf16x2 %0, %1, %2;" : "=r"(r.y) : "r"(prmt(lo, hi, 0x7362)), "r"(s.y));
  return r;
}

template <int B0, int B1>
__device__ __forceinline__ void stage_boxes(const uint32_t (&pk)[56], uint32_t buf, int warp, int lane) {
  const int r = warp * 16 + (lane & 15), ch = lane >> 4;
#pragma unroll
  for (int b = B0; b < B1; b++) {
#pragma unroll
    for (int p = 0; p < 2; p++) {
      const int cc = p * 2 + ch;
      stmatrix_x4(buf + (b - B0) * 4096 + r * 64 + ((cc ^ ((r >> 1) & 3)) << 4),
                  pk[b * 8 + p * 4], pk[b * 8 + p * 4 + 1], pk[b * 8 + p * 4 + 2], pk[b * 8 + p * 4 + 3]);
    }
  }
}

__global__ void __cluster_dims__(2, 1, 1) __launch_bounds__(384, 1)
nf4_gemm_kernel(const int* __restrict__ q, const __nv_bfloat16* __restrict__ cb, const __nv_bfloat16* __restrict__ am,
                unsigned char* __restrict__ gw, const __nv_bfloat16* __restrict__ x,
                const __grid_constant__ TensorMaps maps) {
  const CUtensorMap& mx = maps.x;
  const CUtensorMap& mo = maps.out;
  extern __shared__ __align__(1024) unsigned char smem_raw[];
  const uint32_t sb = smem_u32(smem_raw);
  const uint32_t epi = sb + STAGES * STB, ring = epi + EPI, bars = ring + 4 * SLOTB;
  const uint32_t cst = bars + 512, cfull = bars + 192;
  auto full = [&](int s) { return bars + s * 8; };
  auto empty = [&](int s) { return bars + 32 + s * 8; };
  auto jdone = [&](int j) { return bars + 64 + j * 8; };
  unsigned int* gflag = (unsigned int*)(gw + (size_t)K * N * 2);
  unsigned int* gepoch = gflag + 256;

  const int c = blockIdx.x, wid = threadIdx.x >> 5, wg = wid >> 2, lane = threadIdx.x & 31, rank = c & 1;
  const int jc = c >> 1, b7 = jc - 36, k7 = (b7 * 37) >> 8;
  const int gidx = jc < 4 ? 15 : jc < 36 ? ((jc - 4) & 7) : 8 + b7 - 7 * k7;
  const int kidx = jc < 4 ? jc : jc < 36 ? ((jc - 4) >> 3) : k7;
  const int mt = (gidx & 7) * 2 + rank, pj = 4 * (gidx >> 3) + kidx;

  const int grp = mt & 3, r0 = (mt >> 2) * 16 + (lane >> 3);
  const int col = pj * BN + wid * 32 + (lane & 7) * 4;
  const uint32_t cstart = clock();
  wait_clock(cstart, grp * T_JOB0_STEP);
  int4 v[4]; uint4 cb0, cb1; uint2 sc0;
  asm volatile("{\n.reg .pred p;\nsetp.lt.s32 p, %30, 7;\n"
               "@p ld.global.nc.v4.u32 {%16,%17,%18,%19}, [%27];\n@p ld.global.nc.v4.u32 {%20,%21,%22,%23}, [%27+16];\n"
               "@p ld.global.nc.v2.u32 {%24,%25}, [%28];\n"
               "@p ld.global.nc.L1::no_allocate.L2::cache_hint.v4.s32 {%0,%1,%2,%3}, [%26], %29;\n"
               "@p ld.global.nc.L1::no_allocate.L2::cache_hint.v4.s32 {%4,%5,%6,%7}, [%26+57344], %29;\n"
               "@p ld.global.nc.L1::no_allocate.L2::cache_hint.v4.s32 {%8,%9,%10,%11}, [%26+114688], %29;\n"
               "@p ld.global.nc.L1::no_allocate.L2::cache_hint.v4.s32 {%12,%13,%14,%15}, [%26+172032], %29;\n}"
               : "=r"(v[0].x), "=r"(v[0].y), "=r"(v[0].z), "=r"(v[0].w), "=r"(v[1].x), "=r"(v[1].y), "=r"(v[1].z), "=r"(v[1].w),
                 "=r"(v[2].x), "=r"(v[2].y), "=r"(v[2].z), "=r"(v[2].w), "=r"(v[3].x), "=r"(v[3].y), "=r"(v[3].z), "=r"(v[3].w),
                 "=r"(cb0.x), "=r"(cb0.y), "=r"(cb0.z), "=r"(cb0.w), "=r"(cb1.x), "=r"(cb1.y), "=r"(cb1.z), "=r"(cb1.w),
                 "=r"(sc0.x), "=r"(sc0.y)
               : "l"(q + (grp * 64 + r0) * N + col), "l"(cb), "l"(am + col), "l"(EVICT_FIRST), "r"(wid));
  auto img_off = [&](int r) {
    const int rr = r & 7;
    return (r >> 3) * 3584 + rr * 64 + ((((lane & 7) >> 1) ^ ((rr >> 1) & 3)) << 4) + (lane & 1) * 8;
  };
  if (threadIdx.x == 288) {
    mbar_init(cfull, 1);
    fence_async_smem();
  } else if (threadIdx.x == 256) {
#pragma unroll
    for (int s = 0; s < STAGES; s++) { mbar_init(full(s), 1); mbar_init(empty(s), 4); }
    asm volatile("fence.mbarrier_init.release.cluster;" ::: "memory");
    fence_async_smem();
  } else if (threadIdx.x == 320) {
#pragma unroll
    for (int j = 0; j < 8; j++) mbar_init(jdone(j), j == 0 ? 7 : 2);
  }
  __syncthreads();
  cluster_arrive();

  if (wg == 2) {
    const int w = wid & 3;
    if (w >= 2) {
      reg_dec<REG_SIDE>();
      const __nv_bfloat16* xq = x + (size_t)(mt * BM + pj * 16 + (lane & 15)) * K;
      for (int i = w - 2; i < 4; i += 2) { wait_clock(cstart, T_XPF0 + i * T_XPF); if (lane < 16) prefetch_l2(xq + i * BK); }
      const uint32_t myring = ring + (w - 2) * 2 * SLOTB + lane * 16;
      mbar_wait(cfull, 0);
      const Lut lut = make_lut(lds128(cst), lds128(cst + 16));
      uint2 sc[7];
#pragma unroll
      for (int g = 0; g < 7; g++) sc[g] = lds64(cst + 32 + g * 64 + (lane & 7) * 8);
      const int rw = r0 + (w - 2) * 8;
#pragma unroll 1
      for (int j = 1; j < 8; j++) {
        const int i = 4 * j + grp;
        wait_clock(cstart, j == 1 ? T_JOB1 + grp * T_JOB1_STEP : T_JOB2 + (i - 8) * T_BLOCK);
        const int* p = q + (size_t)((i & 15) * 64 + rw) * N + (pj + (i >> 4) * 8) * BN + (lane & 7) * 4;
#pragma unroll
        for (int h = 0; h < 2; h++) {
#pragma unroll
          for (int g = 0; g < 7; g++)
            asm volatile("cp.async.cg.shared.global.L2::cache_hint [%0], [%1], 16, %2;"
                         ::"r"(myring + h * SLOTB + g * 512), "l"(p + (size_t)h * 4 * N + g * 32), "l"(EVICT_FIRST) : "memory");
          asm volatile("cp.async.commit_group;" ::: "memory");
        }
        if (j == 4) {
#pragma unroll
          for (int g = 0; g < 7; g++) sc[g] = lds64(cst + 480 + g * 64 + (lane & 7) * 8);
        }
        unsigned char* blk = gw + ((size_t)(pj + (i >> 4) * 8) * KB + (i & 15)) * WB;
#pragma unroll 1
        for (int h = 0; h < 2; h++) {
          if (h == 0) asm volatile("cp.async.wait_group 1;" ::: "memory"); else asm volatile("cp.async.wait_group 0;" ::: "memory");
          uint4 u[7];
#pragma unroll
          for (int g = 0; g < 7; g++) u[g] = lds128(myring + h * SLOTB + g * 512);
          unsigned char* dst = blk + img_off(rw + h * 4);
#pragma unroll
          for (int g = 0; g < 7; g++)
            *(uint2*)(dst + g * 512) = dequant4(make_int4(u[g].x, u[g].y, u[g].z, u[g].w), lut, sc[g]);
        }
        __syncwarp();
        if (lane == 0) mbar_arrive(jdone(j));
      }
      cluster_wait();
    } else if (w == 1) {
      reg_dec<REG_SIDE>();
      if (lane == 0) {
        mbar_expect_tx(cfull, 32 + 2 * 448);
        bulk_load(cst, cb, 32, cfull);
        bulk_load(cst + 32, am + pj * BN, 448, cfull);
        bulk_load(cst + 480, am + (pj + 8) * BN, 448, cfull);
      }
#pragma unroll 1
      for (int j = 0; j < 8; j++) {
        mbar_wait(jdone(j), 0);
        if (lane == 0) asm volatile("red.release.gpu.global.add.u32 [%0], 1;" ::"l"(gflag + pj * 32 + 4 * j + grp) : "memory");
        __syncwarp();
      }
      cluster_wait();
    } else {
      reg_dec<REG_SIDE>();
      if (lane == 0) asm volatile("prefetch.tensormap [%0];" ::"l"(&mx) : "memory");
      const unsigned int epoch = gepoch[c];
      const unsigned int* fl = gflag + pj * 32 + lane;
      const __nv_bfloat16* xp = x + (size_t)(mt * BM + pj * 16 + (lane & 15)) * K;
      cluster_wait();
      const unsigned int target = (epoch + 1) * 4;
      unsigned int ready = 0;
      int s = 0, ph = 1;
      const unsigned char* wsrc = gw + (size_t)pj * KB * WB + rank * WH;
      auto poll = [&]() {
        unsigned int f;
        asm volatile("ld.relaxed.gpu.global.u32 %0, [%1];" : "=r"(f) : "l"(fl) : "memory");
        return __ballot_sync(~0u, (int)(f - target) >= 0);
      };
      auto acquire = [&]() {
        asm volatile("fence.acquire.gpu;" ::: "memory");
        __syncwarp();
        asm volatile("fence.proxy.async.global;" ::: "memory");
      };
#pragma unroll 1
      for (int i = 0; i < NBLK; i++) {
        const uint32_t xs = sb + s * STB, ws = xs + XB + rank * WH, fb = full(s);
        const int kc = (i & 15) * BK;
        for (int n = 0; n < (1 << 22) && !((ready >> i) & 1) && !mbar_test(empty(s), ph); n++) {
          const unsigned int r = poll();
          if ((r >> i) & 1) { acquire(); ready = r; }
        }
        if ((ready >> i) & 1) {
          if (i == 2 || i == 3) mbar_wait(full(i - 2), 0);
          mbar_wait(empty(s), ph);
          issue_stage<true, true, true>(fb, xs, &mx, kc, mt * BM, ws, wsrc);
        } else {
          mbar_wait(empty(s), ph);
          if (i >= 4) issue_stage<true, true, false>(fb, xs, &mx, kc, mt * BM, ws, wsrc);
          int spins = 0;
          do {
            ready = poll();
            if (++spins > (1 << 22)) asm volatile("trap;");
          } while (!((ready >> i) & 1));
          acquire();
          if (i >= 4) {
            issue_stage<false, false, true>(fb, xs, &mx, kc, mt * BM, ws, wsrc);
          } else {
            if (i >= 2) mbar_wait(full(i - 2), 0);
            issue_stage<true, true, true>(fb, xs, &mx, kc, mt * BM, ws, wsrc);
          }
        }
        if (i + 4 < KB && lane < 16) prefetch_l2(xp + (i + 4) * BK);
        wsrc += (i == KB - 1) ? (size_t)(7 * KB + 1) * WB : (size_t)WB;
        if (++s == STAGES) { s = 0; ph ^= 1; }
      }
      if (lane == 0) gepoch[c] = epoch + 1;
    }
  } else {
    const int warp = wid & 3;
    if (wid < 7) {
      const Lut lut = make_lut(cb0, cb1);
      unsigned char* blk = gw + ((size_t)pj * KB + grp) * WB + wid * 512;
#pragma unroll
      for (int g = 0; g < 4; g++) *(uint2*)(blk + img_off(r0 + g * 4)) = dequant4(v[g], lut, sc0);
      __syncwarp();
      if (lane == 0) mbar_arrive(jdone(0));
    }
    reg_inc<REG_CONSUMER>();
    const bool leader = (threadIdx.x & 127) == 0;
    if (leader) asm volatile("prefetch.tensormap [%0];" ::"l"(&mo) : "memory");
    float acc[112];
    const uint32_t empty_peer = mapa(empty(0), rank ^ 1);
    cluster_wait();
    int s = 0, ph = 0;
    auto mma_block = [&](int st, int first) {
      const uint64_t da = make_desc(sb + st * STB + wg * 8192, 16, 1024, 1), db = make_desc(sb + st * STB + XB, 512, 3584, 2);
      wg_fence();
#pragma unroll
      for (int k = 0; k < 4; k++) wgmma_n224<0>(acc, da + k * 2, db + k * 448, !(first && k == 0));
      wg_commit();
    };
    auto release_prev = [&]() {
      const int st = s == 0 ? STAGES - 1 : s - 1;
      if (leader) { mbar_arrive(empty(st)); mbar_arrive_remote(empty_peer + st * 8); }
    };
    auto advance = [&]() { if (++s == STAGES) { s = 0; ph ^= 1; } };

#pragma unroll 1
    for (int kb = 0; kb < KB; kb++) {
      mbar_wait(full(s), ph);
      mma_block(s, kb == 0);
      wg_wait<1>();
      if (kb > 0) release_prev();
      advance();
    }
    wg_wait<0>();
    release_prev();
    uint32_t pk[56];
#pragma unroll
    for (int i = 0; i < 56; i++) pk[i] = pack_bf16(acc[2 * i], acc[2 * i + 1]);

    const uint32_t ebuf = epi + wg * 12288;
    const int row0 = mt * BM + wg * 64, col0 = pj * BN, col1 = (pj + 8) * BN;
#pragma unroll
    for (int kb = 0; kb < 7; kb++) {
      mbar_wait(full(s), ph);
      mma_block(s, kb == 0);
      if (kb > 0) { wg_wait<1>(); release_prev(); }
      advance();
      if (kb >= 3) { if (leader) bulk_wait_read<2>(); wg_sync(wg); }
      const uint32_t buf = ebuf + (kb % 3) * 4096;
      if (kb == 0) stage_boxes<0, 1>(pk, buf, warp, lane);
      if (kb == 1) stage_boxes<1, 2>(pk, buf, warp, lane);
      if (kb == 2) stage_boxes<2, 3>(pk, buf, warp, lane);
      if (kb == 3) stage_boxes<3, 4>(pk, buf, warp, lane);
      if (kb == 4) stage_boxes<4, 5>(pk, buf, warp, lane);
      if (kb == 5) stage_boxes<5, 6>(pk, buf, warp, lane);
      if (kb == 6) stage_boxes<6, 7>(pk, buf, warp, lane);
      fence_async_smem();
      wg_sync(wg);
      if (leader) { tma_store_2d(&mo, buf, col0 + kb * 32, row0, EVICT_FIRST); bulk_commit(); }
    }
#pragma unroll 1
    for (int kb = 7; kb < KB; kb++) {
      const bool hold = kb == KB - 4 && wg == 1;
      if (hold) { wg_wait<0>(); release_prev(); asm volatile("bar.sync 4, 256;" ::: "memory"); }
      mbar_wait(full(s), ph);
      mma_block(s, 0);
      wg_wait<1>();
      if (kb <= KB - 4 && !hold) release_prev();
      if (kb == 10 && leader) bulk_wait_read<0>();
      if (kb == KB - 1 && wg == 0) asm volatile("bar.arrive 4, 256;" ::: "memory");
      advance();
    }
    wg_wait<0>();
    const uint32_t x0 = sb + wg * 8192, x1 = sb + STB + wg * 8192;
    auto box_buf = [&](int b) { return b < 3 ? ebuf + b * 4096 : b < 5 ? x0 + (b - 3) * 4096 : x1 + (b - 5) * 4096; };
#pragma unroll
    for (int b = 0; b < 7; b++) {
#pragma unroll
      for (int i = b * 8; i < b * 8 + 8; i++) pk[i] = pack_bf16(acc[2 * i], acc[2 * i + 1]);
      const int r = warp * 16 + (lane & 15), ch = lane >> 4;
#pragma unroll
      for (int p = 0; p < 2; p++)
        stmatrix_x4(box_buf(b) + r * 64 + (((p * 2 + ch) ^ ((r >> 1) & 3)) << 4),
                    pk[b * 8 + p * 4], pk[b * 8 + p * 4 + 1], pk[b * 8 + p * 4 + 2], pk[b * 8 + p * 4 + 3]);
      if (b == 1 || b == 3 || b == 6) {
        fence_async_smem();
        wg_sync(wg);
        const int b0 = b == 1 ? 0 : b == 3 ? 2 : 4;
        if (lane == 0 && warp <= b - b0) tma_store_2d(&mo, box_buf(b0 + warp), col1 + (b0 + warp) * 32, row0, EVICT_FIRST);
      }
    }
    if (lane == 0) { bulk_commit(); bulk_wait_read<0>(); }
  }
}

typedef CUresult (*EncodeTiledFn)(CUtensorMap*, CUtensorMapDataType, cuuint32_t, void*, const cuuint64_t*, const cuuint64_t*,
                                  const cuuint32_t*, const cuuint32_t*, CUtensorMapInterleave, CUtensorMapSwizzle,
                                  CUtensorMapL2promotion, CUtensorMapFloatOOBfill);

void make_map_2d(EncodeTiledFn enc, CUtensorMap* m, void* base, uint64_t inner, uint64_t outer, uint32_t b0, uint32_t b1,
                 CUtensorMapSwizzle sw, CUtensorMapL2promotion prom) {
  cuuint64_t dims[2] = {inner, outer};
  cuuint64_t strides[1] = {inner * 2};
  cuuint32_t box[2] = {b0, b1};
  cuuint32_t es[2] = {1, 1};
  enc(m, CU_TENSOR_MAP_DATA_TYPE_BFLOAT16, 2, base, dims, strides, box, es, CU_TENSOR_MAP_INTERLEAVE_NONE, sw, prom,
      CU_TENSOR_MAP_FLOAT_OOB_FILL_NONE);
}

}

extern "C" void kernel_launch(void* const* d_in, const int* in_sizes, int n_in, void* d_out, int out_size) {
  (void)in_sizes; (void)n_in; (void)out_size;
  static EncodeTiledFn enc = nullptr;
  static void* scratch = nullptr;
  if (!enc) {
    void* f = nullptr;
    cudaDriverEntryPointQueryResult qr;
    cudaGetDriverEntryPoint("cuTensorMapEncodeTiled", &f, cudaEnableDefault, &qr);
    enc = (EncodeTiledFn)f;
    cudaFuncSetAttribute(nf4_gemm_kernel, cudaFuncAttributeMaxDynamicSharedMemorySize, SMEM);
    cudaGetSymbolAddress(&scratch, g_scratch);
  }
  TensorMaps maps;
  make_map_2d(enc, &maps.x, d_in[0], K, M, BK, BM, CU_TENSOR_MAP_SWIZZLE_128B, CU_TENSOR_MAP_L2_PROMOTION_L2_128B);
  make_map_2d(enc, &maps.out, d_out, N, M, 32, 64, CU_TENSOR_MAP_SWIZZLE_64B, CU_TENSOR_MAP_L2_PROMOTION_NONE);
  nf4_gemm_kernel<<<128, 384, SMEM, cudaStreamPerThread>>>(
      (const int*)d_in[1], (const __nv_bfloat16*)d_in[2], (const __nv_bfloat16*)d_in[3], (unsigned char*)scratch,
      (const __nv_bfloat16*)d_in[0], maps);
}
```

```cpp
#include <cuda_runtime.h>
#include <cuda_bf16.h>
#include <cuda.h>
#include <stdint.h>

namespace {

constexpr int M = 2048, N = 3584, K = 1024;
constexpr int BM = 128, BN = 224, BK = 64, KB = K / BK, STAGES = 4, NBLK = 2 * KB;
constexpr int XB = BM * BK * 2, WB = BN * BK * 2, STB = XB + WB, WH = WB / 2;
constexpr int EPI = 24576, SLOTB = 3584;
constexpr int SMEM = STAGES * STB + EPI + 4 * SLOTB + 512 + 1024;
constexpr int REG_CONSUMER = 208, REG_SIDE = 88;
constexpr int T_JOB0_STEP = 300, T_XPF0 = 1400, T_XPF = 200, T_JOB1 = 2600, T_JOB1_STEP = 350, T_JOB2 = 4200, T_BLOCK = 700;
constexpr uint64_t EVICT_FIRST = 0x12F0000000000000ull;

struct alignas(128) TensorMaps { CUtensorMap x, out; };

__device__ __align__(1024) unsigned char g_scratch[(size_t)K * N * 2 + 2048];

template <int OFF>
__device__ __forceinline__ void wgmma_n224(float (&d)[112], uint64_t da, uint64_t db, int scale_d) {
  asm volatile("{\n.reg .pred p;\nsetp.ne.b32 p, %114, 0;\n"
      "wgmma.mma_async.sync.aligned.m64n224k16.f32.bf16.bf16 {"
      "%0, %1, %2, %3, %4, %5, %6, %7, %8, %9, %10, %11, %12, %13, %14, %15, "
      "%16, %17, %18, %19, %20, %21, %22, %23, %24, %25, %26, %27, %28, %29, %30, %31, "
      "%32, %33, %34, %35, %36, %37, %38, %39, %40, %41, %42, %43, %44, %45, %46, %47, "
      "%48, %49, %50, %51, %52, %53, %54, %55, %56, %57, %58, %59, %60, %61, %62, %63, "
      "%64, %65, %66, %67, %68, %69, %70, %71, %72, %73, %74, %75, %76, %77, %78, %79, "
      "%80, %81, %82, %83, %84, %85, %86, %87, %88, %89, %90, %91, %92, %93, %94, %95, "
      "%96, %97, %98, %99, %100, %101, %102, %103, %104, %105, %106, %107, %108, %109, %110, %111"
      "}, %112, %113, p, 1, 1, 0, 1;\n}\n"
      : "+f"(d[OFF+0]), "+f"(d[OFF+1]), "+f"(d[OFF+2]), "+f"(d[OFF+3]), "+f"(d[OFF+4]), "+f"(d[OFF+5]), "+f"(d[OFF+6]), "+f"(d[OFF+7]),
      "+f"(d[OFF+8]), "+f"(d[OFF+9]), "+f"(d[OFF+10]), "+f"(d[OFF+11]), "+f"(d[OFF+12]), "+f"(d[OFF+13]), "+f"(d[OFF+14]), "+f"(d[OFF+15]),
      "+f"(d[OFF+16]), "+f"(d[OFF+17]), "+f"(d[OFF+18]), "+f"(d[OFF+19]), "+f"(d[OFF+20]), "+f"(d[OFF+21]), "+f"(d[OFF+22]), "+f"(d[OFF+23]),
      "+f"(d[OFF+24]), "+f"(d[OFF+25]), "+f"(d[OFF+26]), "+f"(d[OFF+27]), "+f"(d[OFF+28]), "+f"(d[OFF+29]), "+f"(d[OFF+30]), "+f"(d[OFF+31]),
      "+f"(d[OFF+32]), "+f"(d[OFF+33]), "+f"(d[OFF+34]), "+f"(d[OFF+35]), "+f"(d[OFF+36]), "+f"(d[OFF+37]), "+f"(d[OFF+38]), "+f"(d[OFF+39]),
      "+f"(d[OFF+40]), "+f"(d[OFF+41]), "+f"(d[OFF+42]), "+f"(d[OFF+43]), "+f"(d[OFF+44]), "+f"(d[OFF+45]), "+f"(d[OFF+46]), "+f"(d[OFF+47]),
      "+f"(d[OFF+48]), "+f"(d[OFF+49]), "+f"(d[OFF+50]), "+f"(d[OFF+51]), "+f"(d[OFF+52]), "+f"(d[OFF+53]), "+f"(d[OFF+54]), "+f"(d[OFF+55]),
      "+f"(d[OFF+56]), "+f"(d[OFF+57]), "+f"(d[OFF+58]), "+f"(d[OFF+59]), "+f"(d[OFF+60]), "+f"(d[OFF+61]), "+f"(d[OFF+62]), "+f"(d[OFF+63]),
      "+f"(d[OFF+64]), "+f"(d[OFF+65]), "+f"(d[OFF+66]), "+f"(d[OFF+67]), "+f"(d[OFF+68]), "+f"(d[OFF+69]), "+f"(d[OFF+70]), "+f"(d[OFF+71]),
      "+f"(d[OFF+72]), "+f"(d[OFF+73]), "+f"(d[OFF+74]), "+f"(d[OFF+75]), "+f"(d[OFF+76]), "+f"(d[OFF+77]), "+f"(d[OFF+78]), "+f"(d[OFF+79]),
      "+f"(d[OFF+80]), "+f"(d[OFF+81]), "+f"(d[OFF+82]), "+f"(d[OFF+83]), "+f"(d[OFF+84]), "+f"(d[OFF+85]), "+f"(d[OFF+86]), "+f"(d[OFF+87]),
      "+f"(d[OFF+88]), "+f"(d[OFF+89]), "+f"(d[OFF+90]), "+f"(d[OFF+91]), "+f"(d[OFF+92]), "+f"(d[OFF+93]), "+f"(d[OFF+94]), "+f"(d[OFF+95]),
      "+f"(d[OFF+96]), "+f"(d[OFF+97]), "+f"(d[OFF+98]), "+f"(d[OFF+99]), "+f"(d[OFF+100]), "+f"(d[OFF+101]), "+f"(d[OFF+102]), "+f"(d[OFF+103]),
      "+f"(d[OFF+104]), "+f"(d[OFF+105]), "+f"(d[OFF+106]), "+f"(d[OFF+107]), "+f"(d[OFF+108]), "+f"(d[OFF+109]), "+f"(d[OFF+110]), "+f"(d[OFF+111])
      : "l"(da), "l"(db), "r"(scale_d));
}

__device__ __forceinline__ uint32_t smem_u32(const void* p) { return (uint32_t)__cvta_generic_to_shared(p); }
__device__ __forceinline__ void mbar_init(uint32_t bar, uint32_t cnt) {
  asm volatile("mbarrier.init.shared::cta.b64 [%0], %1;" ::"r"(bar), "r"(cnt) : "memory");
}
__device__ __forceinline__ void mbar_expect_tx(uint32_t bar, uint32_t bytes) {
  asm volatile("mbarrier.arrive.expect_tx.shared::cta.b64 _, [%0], %1;" ::"r"(bar), "r"(bytes) : "memory");
}
__device__ __forceinline__ void mbar_arrive(uint32_t bar) {
  asm volatile("mbarrier.arrive.shared::cta.b64 _, [%0];" ::"r"(bar) : "memory");
}
__device__ __forceinline__ void mbar_arrive_remote(uint32_t cluster_addr) {
  asm volatile("mbarrier.arrive.shared::cluster.b64 _, [%0];" ::"r"(cluster_addr) : "memory");
}
__device__ __forceinline__ bool mbar_test(uint32_t bar, uint32_t parity) {
  uint32_t ok;
  asm volatile("{\n.reg .pred p;\nmbarrier.test_wait.parity.shared::cta.b64 p, [%1], %2;\nselp.u32 %0, 1, 0, p;\n}"
               : "=r"(ok) : "r"(bar), "r"(parity) : "memory");
  return ok;
}
__device__ __forceinline__ void mbar_wait(uint32_t bar, uint32_t parity) {
  asm volatile(
      "{\n.reg .pred p;\n.reg .u32 n;\nmov.u32 n, 0;\n"
      "LAB_WAIT:\nmbarrier.try_wait.parity.shared::cta.b64 p, [%0], %1;\n@p bra LAB_DONE;\n"
      "add.u32 n, n, 1;\nsetp.lt.u32 p, n, 1048576;\n@p bra LAB_WAIT;\ntrap;\nLAB_DONE:\n}" ::"r"(bar), "r"(parity) : "memory");
}
__device__ __forceinline__ void bulk_load(uint32_t dst, const void* src, uint32_t bytes, uint32_t bar) {
  asm volatile("cp.async.bulk.shared::cluster.global.mbarrier::complete_tx::bytes [%0], [%1], %2, [%3];"
               ::"r"(dst), "l"(src), "r"(bytes), "r"(bar) : "memory");
}
__device__ __forceinline__ void tma_store_2d(const CUtensorMap* m, uint32_t src, int c0, int c1, uint64_t pol) {
  asm volatile("cp.async.bulk.tensor.2d.global.shared::cta.bulk_group.L2::cache_hint [%0, {%2, %3}], [%1], %4;"
               ::"l"(m), "r"(src), "r"(c0), "r"(c1), "l"(pol) : "memory");
}
__device__ __forceinline__ void tma_store_2d_elect(const CUtensorMap* m, uint32_t src, int c0, int c1, uint64_t pol) {
  asm volatile("{\n.reg .pred p;\nelect.sync _|p, 0xffffffff;\n"
               "@p cp.async.bulk.tensor.2d.global.shared::cta.bulk_group.L2::cache_hint [%0, {%2, %3}], [%1], %4;\n"
               "@p cp.async.bulk.commit_group;\n}"
               ::"l"(m), "r"(src), "r"(c0), "r"(c1), "l"(pol) : "memory");
}
__device__ __forceinline__ void bulk_commit() { asm volatile("cp.async.bulk.commit_group;" ::: "memory"); }
template <int NG> __device__ __forceinline__ void bulk_wait_read() { asm volatile("cp.async.bulk.wait_group.read %0;" ::"n"(NG) : "memory"); }
__device__ __forceinline__ void fence_async_smem() { asm volatile("fence.proxy.async.shared::cta;" ::: "memory"); }
__device__ __forceinline__ void wg_fence() { asm volatile("wgmma.fence.sync.aligned;" ::: "memory"); }
__device__ __forceinline__ void wg_commit() { asm volatile("wgmma.commit_group.sync.aligned;" ::: "memory"); }
template <int NG> __device__ __forceinline__ void wg_wait() { asm volatile("wgmma.wait_group.sync.aligned %0;" ::"n"(NG) : "memory"); }
__device__ __forceinline__ void cluster_arrive() { asm volatile("barrier.cluster.arrive.relaxed.aligned;" ::: "memory"); }
__device__ __forceinline__ void cluster_wait() { asm volatile("barrier.cluster.wait.aligned;" ::: "memory"); }
template <int R> __device__ __forceinline__ void reg_inc() { asm volatile("setmaxnreg.inc.sync.aligned.u32 %0;" ::"n"(R)); }
template <int R> __device__ __forceinline__ void reg_dec() { asm volatile("setmaxnreg.dec.sync.aligned.u32 %0;" ::"n"(R)); }
__device__ __forceinline__ void wg_sync(int wg) {
  if (wg == 0) asm volatile("bar.sync 1, 128;" ::: "memory"); else asm volatile("bar.sync 2, 128;" ::: "memory");
}
__device__ __forceinline__ uint32_t mapa(uint32_t a, uint32_t cta) {
  uint32_t r; asm("mapa.shared::cluster.u32 %0, %1, %2;" : "=r"(r) : "r"(a), "r"(cta)); return r;
}
__device__ __forceinline__ uint64_t make_desc(uint32_t addr, uint32_t lbo, uint32_t sbo, uint32_t mode) {
  return (uint64_t)((addr & 0x3FFFF) >> 4) | ((uint64_t)(lbo >> 4) << 16) | ((uint64_t)(sbo >> 4) << 32) | ((uint64_t)mode << 62);
}
__device__ __forceinline__ uint32_t pack_bf16(float lo, float hi) {
  uint32_t r; asm("cvt.rn.bf16x2.f32 %0, %1, %2;" : "=r"(r) : "f"(hi), "f"(lo)); return r;
}
__device__ __forceinline__ void stmatrix_x4(uint32_t addr, uint32_t a, uint32_t b, uint32_t c, uint32_t d) {
  asm volatile("stmatrix.sync.aligned.m8n8.x4.shared.b16 [%0], {%1,%2,%3,%4};" ::"r"(addr), "r"(a), "r"(b), "r"(c), "r"(d) : "memory");
}
__device__ __forceinline__ void prefetch_l2(const void* p) { asm volatile("prefetch.global.L2 [%0];" ::"l"(p) : "memory"); }
__device__ __forceinline__ void wait_clock(uint32_t t0, int d) { while ((int)((uint32_t)clock() - t0) < d) {} }
__device__ __forceinline__ void stg64(unsigned char* p, uint2 v) {
  asm volatile("st.global.v2.u32 [%0], {%1,%2};" ::"l"(p), "r"(v.x), "r"(v.y) : "memory");
}
__device__ __forceinline__ uint2 lds64(uint32_t a) {
  uint2 r; asm volatile("ld.shared.v2.u32 {%0,%1}, [%2];" : "=r"(r.x), "=r"(r.y) : "r"(a) : "memory"); return r;
}
__device__ __forceinline__ uint4 lds128(uint32_t a) {
  uint4 r; asm volatile("ld.shared.v4.u32 {%0,%1,%2,%3}, [%4];" : "=r"(r.x), "=r"(r.y), "=r"(r.z), "=r"(r.w) : "r"(a) : "memory"); return r;
}

template <bool ARM, bool X, bool W>
__device__ __forceinline__ void issue_stage(uint32_t bar, uint32_t xdst, const CUtensorMap* m, int c0, int c1,
                                            uint32_t wdst, const void* wsrc) {
  asm volatile("{\n.reg .pred p, px, pw, pa;\nelect.sync _|p, 0xffffffff;\n"
               "setp.ne.and.u32 pa, %7, 0, p;\nsetp.ne.and.u32 px, %8, 0, p;\nsetp.ne.and.u32 pw, %9, 0, p;\n"
               "@pa mbarrier.arrive.expect_tx.shared::cta.b64 _, [%0], %10;\n"
               "@pw cp.async.bulk.shared::cluster.global.mbarrier::complete_tx::bytes.multicast::cluster [%5], [%6], %11, [%0], %12;\n"
               "@px cp.async.bulk.tensor.2d.shared::cluster.global.mbarrier::complete_tx::bytes [%1], [%2, {%3, %4}], [%0];\n}"
               ::"r"(bar), "r"(xdst), "l"(m), "r"(c0), "r"(c1), "r"(wdst), "l"(wsrc), "n"((int)ARM), "n"((int)X), "n"((int)W),
                 "n"(STB), "n"(WH), "h"((uint16_t)3) : "memory");
}

struct Lut { uint32_t lo[4], hi[4], m4, id; };
__device__ __forceinline__ uint32_t prmt(uint32_t a, uint32_t b, uint32_t s) {
  uint32_t r; asm("prmt.b32 %0, %1, %2, %3;" : "=r"(r) : "r"(a), "r"(b), "r"(s)); return r;
}
__device__ __forceinline__ Lut make_lut(uint4 c0, uint4 c1) {
  Lut l;
  l.lo[0] = prmt(c0.x, c0.y, 0x6420); l.hi[0] = prmt(c0.x, c0.y, 0x7531);
  l.lo[1] = prmt(c0.z, c0.w, 0x6420); l.hi[1] = prmt(c0.z, c0.w, 0x7531);
  l.lo[2] = prmt(c1.x, c1.y, 0x6420); l.hi[2] = prmt(c1.x, c1.y, 0x7531);
  l.lo[3] = prmt(c1.z, c1.w, 0x6420); l.hi[3] = prmt(c1.z, c1.w, 0x7531);
  l.m4 = 0x4444; l.id = 0x3210;
  return l;
}
__device__ __forceinline__ uint2 dequant4(int4 v, const Lut& l, uint2 s) {
  const uint32_t sel = (uint32_t)(v.x + v.y * 16) + (uint32_t)(v.z + v.w * 16) * 256;
  const uint32_t s7 = sel & 0x7777;
  uint32_t s2;
  asm("lop3.b32 %0, %1, %2, %3, 0xEA;" : "=r"(s2) : "r"(sel >> 1), "r"(l.m4), "r"(l.id));
  const uint32_t lo = prmt(prmt(l.lo[0], l.lo[1], s7), prmt(l.lo[2], l.lo[3], s7), s2);
  const uint32_t hi = prmt(prmt(l.hi[0], l.hi[1], s7), prmt(l.hi[2], l.hi[3], s7), s2);
  uint2 r;
  asm("mul.rn.bf16x2 %0, %1, %2;" : "=r"(r.x) : "r"(prmt(lo, hi, 0x5140)), "r"(s.x));
  asm("mul.rn.bf16x2 %0, %1, %2;" : "=r"(r.y) : "r"(prmt(lo, hi, 0x7362)), "r"(s.y));
  return r;
}

template <int B0, int B1>
__device__ __forceinline__ void stage_boxes(const uint32_t (&pk)[56], uint32_t buf, int warp, int lane) {
  const int r = warp * 16 + (lane & 15), ch = lane >> 4;
#pragma unroll
  for (int b = B0; b < B1; b++) {
#pragma unroll
    for (int p = 0; p < 2; p++) {
      const int cc = p * 2 + ch;
      stmatrix_x4(buf + (b - B0) * 4096 + r * 64 + ((cc ^ ((r >> 1) & 3)) << 4),
                  pk[b * 8 + p * 4], pk[b * 8 + p * 4 + 1], pk[b * 8 + p * 4 + 2], pk[b * 8 + p * 4 + 3]);
    }
  }
}

__global__ void __cluster_dims__(2, 1, 1) __launch_bounds__(384, 1)
nf4_gemm_kernel(const int* __restrict__ q, const __nv_bfloat16* __restrict__ cb, const __nv_bfloat16* __restrict__ am,
                unsigned char* __restrict__ gw, const __nv_bfloat16* __restrict__ x,
                const __grid_constant__ TensorMaps maps) {
  const CUtensorMap& mx = maps.x;
  const CUtensorMap& mo = maps.out;
  extern __shared__ __align__(1024) unsigned char smem_raw[];
  const uint32_t sb = smem_u32(smem_raw);
  const uint32_t epi = sb + STAGES * STB, ring = epi + EPI, bars = ring + 4 * SLOTB;
  const uint32_t cst = bars + 512, cfull = bars + 192;
  auto full = [&](int s) { return bars + s * 8; };
  auto empty = [&](int s) { return bars + 32 + s * 8; };
  auto jdone = [&](int j) { return bars + 64 + j * 8; };
  unsigned int* gflag = (unsigned int*)(gw + (size_t)K * N * 2);
  unsigned int* gepoch = gflag + 256;

  const int c = blockIdx.x, wid = threadIdx.x >> 5, wg = wid >> 2, lane = threadIdx.x & 31, rank = c & 1;
  const int jc = c >> 1, b7 = jc - 36, k7 = (b7 * 37) >> 8;
  const int gidx = jc < 4 ? 15 : jc < 36 ? ((jc - 4) & 7) : 8 + b7 - 7 * k7;
  const int kidx = jc < 4 ? jc : jc < 36 ? ((jc - 4) >> 3) : k7;
  const int mt = (gidx & 7) * 2 + rank, pj = 4 * (gidx >> 3) + kidx;

  const int grp = mt & 3, r0 = (mt >> 2) * 16 + (lane >> 3);
  const int col = pj * BN + wid * 32 + (lane & 7) * 4;
  const uint32_t cstart = clock();
  wait_clock(cstart, grp * T_JOB0_STEP);
  int4 v[4]; uint4 cb0, cb1; uint2 sc0;
  asm volatile("{\n.reg .pred p;\nsetp.lt.s32 p, %30, 7;\n"
               "@p ld.global.nc.L1::no_allocate.L2::cache_hint.v4.s32 {%0,%1,%2,%3}, [%26], %29;\n"
               "@p ld.global.nc.L1::no_allocate.L2::cache_hint.v4.s32 {%4,%5,%6,%7}, [%26+57344], %29;\n"
               "@p ld.global.nc.L1::no_allocate.L2::cache_hint.v4.s32 {%8,%9,%10,%11}, [%26+114688], %29;\n"
               "@p ld.global.nc.L1::no_allocate.L2::cache_hint.v4.s32 {%12,%13,%14,%15}, [%26+172032], %29;\n"
               "@p ld.global.nc.v4.u32 {%16,%17,%18,%19}, [%27];\n@p ld.global.nc.v4.u32 {%20,%21,%22,%23}, [%27+16];\n"
               "@p ld.global.nc.v2.u32 {%24,%25}, [%28];\n}"
               : "=r"(v[0].x), "=r"(v[0].y), "=r"(v[0].z), "=r"(v[0].w), "=r"(v[1].x), "=r"(v[1].y), "=r"(v[1].z), "=r"(v[1].w),
                 "=r"(v[2].x), "=r"(v[2].y), "=r"(v[2].z), "=r"(v[2].w), "=r"(v[3].x), "=r"(v[3].y), "=r"(v[3].z), "=r"(v[3].w),
                 "=r"(cb0.x), "=r"(cb0.y), "=r"(cb0.z), "=r"(cb0.w), "=r"(cb1.x), "=r"(cb1.y), "=r"(cb1.z), "=r"(cb1.w),
                 "=r"(sc0.x), "=r"(sc0.y)
               : "l"(q + (grp * 64 + r0) * N + col), "l"(cb), "l"(am + col), "l"(EVICT_FIRST), "r"(wid));
  if (threadIdx.x == 288) {
    mbar_init(cfull, 1);
    fence_async_smem();
  } else if (threadIdx.x == 256) {
#pragma unroll
    for (int s = 0; s < STAGES; s++) { mbar_init(full(s), 1); mbar_init(empty(s), 4); }
    asm volatile("fence.mbarrier_init.release.cluster;" ::: "memory");
    fence_async_smem();
  } else if (threadIdx.x == 320) {
#pragma unroll
    for (int j = 0; j < 8; j++) mbar_init(jdone(j), j == 0 ? 7 : 2);
  }
  __syncthreads();
  cluster_arrive();
  const int lo4 = (lane >> 3) * 64 + ((((lane & 7) >> 1) ^ (lane >> 4)) << 4) + (lane & 1) * 8;
  const int hi4 = (lo4 ^ 32) + 256;

  if (wg == 2) {
    reg_dec<REG_SIDE>();
    const int w = __shfl_sync(~0u, wid & 3, 0);
    if (w >= 2) {
      const __nv_bfloat16* xq = x + (size_t)(mt * BM + pj * 16 + (lane & 15)) * K;
      for (int i = w - 2; i < 4; i += 2) { wait_clock(cstart, T_XPF0 + i * T_XPF); if (lane < 16) prefetch_l2(xq + i * BK); }
      const uint32_t myring = ring + (w - 2) * 2 * SLOTB + lane * 16;
      mbar_wait(cfull, 0);
      const Lut lut = make_lut(lds128(cst), lds128(cst + 16));
      uint2 sc[7];
#pragma unroll
      for (int g = 0; g < 7; g++) sc[g] = lds64(cst + 32 + g * 64 + (lane & 7) * 8);
      const int rw = r0 + (w - 2) * 8;
#pragma unroll 1
      for (int j = 1; j < 8; j++) {
        const int i = 4 * j + grp;
        wait_clock(cstart, j == 1 ? T_JOB1 + grp * T_JOB1_STEP : T_JOB2 + (i - 8) * T_BLOCK);
        const int* p = q + (size_t)((i & 15) * 64 + rw) * N + (pj + (i >> 4) * 8) * BN + (lane & 7) * 4;
#pragma unroll
        for (int h = 0; h < 2; h++) {
#pragma unroll
          for (int g = 0; g < 7; g++)
            asm volatile("cp.async.cg.shared.global.L2::cache_hint [%0], [%1], 16, %2;"
                         ::"r"(myring + h * SLOTB + g * 512), "l"(p + (size_t)h * 4 * N + g * 32), "l"(EVICT_FIRST) : "memory");
          asm volatile("cp.async.commit_group;" ::: "memory");
        }
        if (j == 4) {
#pragma unroll
          for (int g = 0; g < 7; g++) sc[g] = lds64(cst + 480 + g * 64 + (lane & 7) * 8);
        }
        unsigned char* blk = gw + ((size_t)(pj + (i >> 4) * 8) * KB + (i & 15)) * WB + ((mt >> 2) * 2 + w - 2) * 3584;
#pragma unroll 1
        for (int h = 0; h < 2; h++) {
          if (h == 0) asm volatile("cp.async.wait_group 1;" ::: "memory"); else asm volatile("cp.async.wait_group 0;" ::: "memory");
          uint4 u[7];
#pragma unroll
          for (int g = 0; g < 7; g++) u[g] = lds128(myring + h * SLOTB + g * 512);
          unsigned char* dst = blk + (h ? hi4 : lo4);
#pragma unroll
          for (int g = 0; g < 7; g++)
            *(uint2*)(dst + g * 512) = dequant4(make_int4(u[g].x, u[g].y, u[g].z, u[g].w), lut, sc[g]);
        }
        __syncwarp();
        if (lane == 0) mbar_arrive(jdone(j));
      }
      cluster_wait();
    } else if (w == 1) {
      if (lane == 0) {
        mbar_expect_tx(cfull, 32 + 2 * 448);
        bulk_load(cst, cb, 32, cfull);
        bulk_load(cst + 32, am + pj * BN, 448, cfull);
        bulk_load(cst + 480, am + (pj + 8) * BN, 448, cfull);
      }
#pragma unroll 1
      for (int j = 0; j < 8; j++) {
        mbar_wait(jdone(j), 0);
        if (lane == 0) asm volatile("red.release.gpu.global.add.u32 [%0], 1;" ::"l"(gflag + pj * 32 + 4 * j + grp) : "memory");
        __syncwarp();
      }
      cluster_wait();
    } else {
      if (lane == 0) asm volatile("prefetch.tensormap [%0];" ::"l"(&mx) : "memory");
      const unsigned int epoch = gepoch[c];
      const unsigned int* fl = gflag + pj * 32 + lane;
      const __nv_bfloat16* xp = x + (size_t)(mt * BM + pj * 16 + (lane & 15)) * K;
      cluster_wait();
      const unsigned int target = (epoch + 1) * 4;
      unsigned int ready = 0;
      int s = 0, ph = 1;
      const unsigned char* wsrc = gw + (size_t)pj * KB * WB + rank * WH;
      auto poll = [&]() {
        unsigned int f;
        asm volatile("ld.relaxed.gpu.global.u32 %0, [%1];" : "=r"(f) : "l"(fl) : "memory");
        return __ballot_sync(~0u, (int)(f - target) >= 0);
      };
      auto acquire = [&]() {
        asm volatile("fence.acquire.gpu;" ::: "memory");
        __syncwarp();
        asm volatile("fence.proxy.async.global;" ::: "memory");
      };
#pragma unroll 1
      for (int i = 0; i < NBLK; i++) {
        const uint32_t xs = sb + s * STB, ws = xs + XB + rank * WH, fb = full(s);
        const int kc = (i & 15) * BK;
        for (int n = 0; n < (1 << 22) && !((ready >> i) & 1) && !mbar_test(empty(s), ph); n++) {
          const unsigned int r = poll();
          if ((r >> i) & 1) { acquire(); ready = r; }
        }
        if ((ready >> i) & 1) {
          if (i == 2 || i == 3) mbar_wait(full(i - 2), 0);
          mbar_wait(empty(s), ph);
          issue_stage<true, true, true>(fb, xs, &mx, kc, mt * BM, ws, wsrc);
        } else {
          mbar_wait(empty(s), ph);
          if (i >= 4) issue_stage<true, true, false>(fb, xs, &mx, kc, mt * BM, ws, wsrc);
          int spins = 0;
          do {
            ready = poll();
            if (++spins > (1 << 22)) asm volatile("trap;");
          } while (!((ready >> i) & 1));
          acquire();
          if (i >= 4) {
            issue_stage<false, false, true>(fb, xs, &mx, kc, mt * BM, ws, wsrc);
          } else {
            if (i >= 2) mbar_wait(full(i - 2), 0);
            issue_stage<true, true, true>(fb, xs, &mx, kc, mt * BM, ws, wsrc);
          }
        }
        if (i + 4 < KB && lane < 16) prefetch_l2(xp + (i + 4) * BK);
        wsrc += (i == KB - 1) ? (size_t)(7 * KB + 1) * WB : (size_t)WB;
        if (++s == STAGES) { s = 0; ph ^= 1; }
      }
      if (lane == 0) gepoch[c] = epoch + 1;
    }
  } else {
    const int widu = __shfl_sync(~0u, wid, 0), warp = widu & 3, wgu = widu >> 2;
    unsigned char* j0lo = gw + (size_t)(pj * KB + grp) * WB + (mt >> 2) * 7168 + wid * 512 + lo4;
    unsigned char* j0hi = j0lo + (hi4 - lo4);
    asm volatile("" : "+l"(j0lo), "+l"(j0hi));
    if (wid < 7) {
      const Lut lut = make_lut(cb0, cb1);
#pragma unroll
      for (int g = 0; g < 4; g++) stg64(((g & 1) ? j0hi : j0lo) + (g >> 1) * 3584, dequant4(v[g], lut, sc0));
      __syncwarp();
      if (lane == 0) mbar_arrive(jdone(0));
    }
    reg_inc<REG_CONSUMER>();
    const bool leader = (threadIdx.x & 127) == 0;
    if (leader) asm volatile("prefetch.tensormap [%0];" ::"l"(&mo) : "memory");
    float acc[112];
    const uint32_t empty_peer = mapa(empty(0), rank ^ 1);
    cluster_wait();
    int s = 0, ph = 0;
    const uint64_t da0 = make_desc(sb + wgu * 8192, 16, 1024, 1), db0 = make_desc(sb + XB, 512, 3584, 2);
    auto mma_block = [&](int first) {
      uint64_t da = da0 + s * (STB >> 4), db = db0 + s * (STB >> 4);
      asm volatile("" : "+l"(da), "+l"(db));
      mbar_wait(full(s), ph);
      wg_fence();
#pragma unroll
      for (int k = 0; k < 4; k++) wgmma_n224<0>(acc, da + k * 2, db + k * 448, !(first && k == 0));
      wg_commit();
    };
    auto release_prev = [&]() {
      const int st = s == 0 ? STAGES - 1 : s - 1;
      if (leader) { mbar_arrive(empty(st)); mbar_arrive_remote(empty_peer + st * 8); }
    };
    auto advance = [&]() { if (++s == STAGES) { s = 0; ph ^= 1; } };

#pragma unroll 1
    for (int kb = 0; kb < KB; kb++) {
      mma_block(kb == 0);
      wg_wait<1>();
      if (kb > 0) release_prev();
      advance();
    }
    wg_wait<0>();
    release_prev();
    uint32_t pk[56];
#pragma unroll
    for (int i = 0; i < 56; i++) pk[i] = pack_bf16(acc[2 * i], acc[2 * i + 1]);

    const uint32_t ebuf = epi + wgu * 12288;
    const int row0 = mt * BM + wgu * 64, col0 = pj * BN, col1 = (pj + 8) * BN;
#pragma unroll
    for (int kb = 0; kb < 7; kb++) {
      mma_block(kb == 0);
      if (kb > 0) { wg_wait<1>(); release_prev(); }
      advance();
      if (kb >= 3) { if (leader) bulk_wait_read<2>(); wg_sync(wgu); }
      const uint32_t buf = ebuf + (kb % 3) * 4096;
      if (kb == 0) stage_boxes<0, 1>(pk, buf, warp, lane);
      if (kb == 1) stage_boxes<1, 2>(pk, buf, warp, lane);
      if (kb == 2) stage_boxes<2, 3>(pk, buf, warp, lane);
      if (kb == 3) stage_boxes<3, 4>(pk, buf, warp, lane);
      if (kb == 4) stage_boxes<4, 5>(pk, buf, warp, lane);
      if (kb == 5) stage_boxes<5, 6>(pk, buf, warp, lane);
      if (kb == 6) stage_boxes<6, 7>(pk, buf, warp, lane);
      fence_async_smem();
      wg_sync(wgu);
      if (leader) { tma_store_2d(&mo, buf, col0 + kb * 32, row0, EVICT_FIRST); bulk_commit(); }
    }
#pragma unroll 1
    for (int kb = 7; kb < KB; kb++) {
      const bool hold = kb == KB - 4 && wgu == 1;
      if (hold) { wg_wait<0>(); release_prev(); asm volatile("bar.sync 4, 256;" ::: "memory"); }
      mma_block(0);
      wg_wait<1>();
      if (kb <= KB - 4 && !hold) release_prev();
      if (kb == 10 && leader) bulk_wait_read<0>();
      if (kb == KB - 1 && wgu == 0) asm volatile("bar.arrive 4, 256;" ::: "memory");
      advance();
    }
    wg_wait<0>();
    const uint32_t x0 = sb + wgu * 8192, x1 = sb + STB + wgu * 8192;
    auto box_buf = [&](int b) { return b < 3 ? ebuf + b * 4096 : b < 5 ? x0 + (b - 3) * 4096 : x1 + (b - 5) * 4096; };
#pragma unroll
    for (int b = 0; b < 7; b++) {
#pragma unroll
      for (int i = b * 8; i < b * 8 + 8; i++) pk[i] = pack_bf16(acc[2 * i], acc[2 * i + 1]);
      const int r = warp * 16 + (lane & 15), ch = lane >> 4;
#pragma unroll
      for (int p = 0; p < 2; p++)
        stmatrix_x4(box_buf(b) + r * 64 + (((p * 2 + ch) ^ ((r >> 1) & 3)) << 4),
                    pk[b * 8 + p * 4], pk[b * 8 + p * 4 + 1], pk[b * 8 + p * 4 + 2], pk[b * 8 + p * 4 + 3]);
      if (b == 1 || b == 3 || b == 6) {
        fence_async_smem();
        wg_sync(wgu);
        const int b0 = b == 1 ? 0 : b == 3 ? 2 : 4;
        if (warp <= b - b0) tma_store_2d_elect(&mo, box_buf(b0 + warp), col1 + (b0 + warp) * 32, row0, EVICT_FIRST);
      }
    }
    bulk_wait_read<0>();
  }
}

typedef CUresult (*EncodeTiledFn)(CUtensorMap*, CUtensorMapDataType, cuuint32_t, void*, const cuuint64_t*, const cuuint64_t*,
                                  const cuuint32_t*, const cuuint32_t*, CUtensorMapInterleave, CUtensorMapSwizzle,
                                  CUtensorMapL2promotion, CUtensorMapFloatOOBfill);

void make_map_2d(EncodeTiledFn enc, CUtensorMap* m, void* base, uint64_t inner, uint64_t outer, uint32_t b0, uint32_t b1,
                 CUtensorMapSwizzle sw, CUtensorMapL2promotion prom) {
  cuuint64_t dims[2] = {inner, outer};
  cuuint64_t strides[1] = {inner * 2};
  cuuint32_t box[2] = {b0, b1};
  cuuint32_t es[2] = {1, 1};
  enc(m, CU_TENSOR_MAP_DATA_TYPE_BFLOAT16, 2, base, dims, strides, box, es, CU_TENSOR_MAP_INTERLEAVE_NONE, sw, prom,
      CU_TENSOR_MAP_FLOAT_OOB_FILL_NONE);
}

}

extern "C" void kernel_launch(void* const* d_in, const int* in_sizes, int n_in, void* d_out, int out_size) {
  (void)in_sizes; (void)n_in; (void)out_size;
  static EncodeTiledFn enc = nullptr;
  static void* scratch = nullptr;
  if (!enc) {
    void* f = nullptr;
    cudaDriverEntryPointQueryResult qr;
    cudaGetDriverEntryPoint("cuTensorMapEncodeTiled", &f, cudaEnableDefault, &qr);
    enc = (EncodeTiledFn)f;
    cudaFuncSetAttribute(nf4_gemm_kernel, cudaFuncAttributeMaxDynamicSharedMemorySize, SMEM);
    cudaGetSymbolAddress(&scratch, g_scratch);
  }
  TensorMaps maps;
  make_map_2d(enc, &maps.x, d_in[0], K, M, BK, BM, CU_TENSOR_MAP_SWIZZLE_128B, CU_TENSOR_MAP_L2_PROMOTION_L2_128B);
  make_map_2d(enc, &maps.out, d_out, N, M, 32, 64, CU_TENSOR_MAP_SWIZZLE_64B, CU_TENSOR_MAP_L2_PROMOTION_NONE);
  nf4_gemm_kernel<<<128, 384, SMEM, cudaStreamPerThread>>>(
      (const int*)d_in[1], (const __nv_bfloat16*)d_in[2], (const __nv_bfloat16*)d_in[3], (unsigned char*)scratch,
      (const __nv_bfloat16*)d_in[0], maps);
}
```

```cpp
#include <cuda_runtime.h>
#include <cuda_bf16.h>
#include <cuda.h>
#include <stdint.h>

namespace {

constexpr int M = 2048, N = 3584, K = 1024;
constexpr int BM = 128, BN = 224, BK = 64, KB = K / BK, STAGES = 4, NBLK = 2 * KB;
constexpr int XB = BM * BK * 2, WB = BN * BK * 2, STB = XB + WB, WH = WB / 2;
constexpr int EPI = 49152;
constexpr int SMEM = STAGES * STB + EPI + 512 + 1024;
constexpr int REG_CONSUMER = 200, REG_SIDE = 104;
constexpr int T_JOB0_STEP = 300, T_XPF0 = 1400, T_XPF = 200, T_JOB1 = 2600, T_JOB1_STEP = 350, T_JOB2 = 4200, T_BLOCK = 700;
constexpr uint64_t EVICT_FIRST = 0x12F0000000000000ull;

struct alignas(128) TensorMaps { CUtensorMap x, out; };

__device__ __align__(1024) unsigned char g_scratch[(size_t)K * N * 2 + 2048];

template <int OFF>
__device__ __forceinline__ void wgmma_n224(float (&d)[112], uint64_t da, uint64_t db, int scale_d) {
  asm volatile("{\n.reg .pred p;\nsetp.ne.b32 p, %114, 0;\n"
      "wgmma.mma_async.sync.aligned.m64n224k16.f32.bf16.bf16 {"
      "%0, %1, %2, %3, %4, %5, %6, %7, %8, %9, %10, %11, %12, %13, %14, %15, "
      "%16, %17, %18, %19, %20, %21, %22, %23, %24, %25, %26, %27, %28, %29, %30, %31, "
      "%32, %33, %34, %35, %36, %37, %38, %39, %40, %41, %42, %43, %44, %45, %46, %47, "
      "%48, %49, %50, %51, %52, %53, %54, %55, %56, %57, %58, %59, %60, %61, %62, %63, "
      "%64, %65, %66, %67, %68, %69, %70, %71, %72, %73, %74, %75, %76, %77, %78, %79, "
      "%80, %81, %82, %83, %84, %85, %86, %87, %88, %89, %90, %91, %92, %93, %94, %95, "
      "%96, %97, %98, %99, %100, %101, %102, %103, %104, %105, %106, %107, %108, %109, %110, %111"
      "}, %112, %113, p, 1, 1, 0, 1;\n}\n"
      : "+f"(d[OFF+0]), "+f"(d[OFF+1]), "+f"(d[OFF+2]), "+f"(d[OFF+3]), "+f"(d[OFF+4]), "+f"(d[OFF+5]), "+f"(d[OFF+6]), "+f"(d[OFF+7]),
      "+f"(d[OFF+8]), "+f"(d[OFF+9]), "+f"(d[OFF+10]), "+f"(d[OFF+11]), "+f"(d[OFF+12]), "+f"(d[OFF+13]), "+f"(d[OFF+14]), "+f"(d[OFF+15]),
      "+f"(d[OFF+16]), "+f"(d[OFF+17]), "+f"(d[OFF+18]), "+f"(d[OFF+19]), "+f"(d[OFF+20]), "+f"(d[OFF+21]), "+f"(d[OFF+22]), "+f"(d[OFF+23]),
      "+f"(d[OFF+24]), "+f"(d[OFF+25]), "+f"(d[OFF+26]), "+f"(d[OFF+27]), "+f"(d[OFF+28]), "+f"(d[OFF+29]), "+f"(d[OFF+30]), "+f"(d[OFF+31]),
      "+f"(d[OFF+32]), "+f"(d[OFF+33]), "+f"(d[OFF+34]), "+f"(d[OFF+35]), "+f"(d[OFF+36]), "+f"(d[OFF+37]), "+f"(d[OFF+38]), "+f"(d[OFF+39]),
      "+f"(d[OFF+40]), "+f"(d[OFF+41]), "+f"(d[OFF+42]), "+f"(d[OFF+43]), "+f"(d[OFF+44]), "+f"(d[OFF+45]), "+f"(d[OFF+46]), "+f"(d[OFF+47]),
      "+f"(d[OFF+48]), "+f"(d[OFF+49]), "+f"(d[OFF+50]), "+f"(d[OFF+51]), "+f"(d[OFF+52]), "+f"(d[OFF+53]), "+f"(d[OFF+54]), "+f"(d[OFF+55]),
      "+f"(d[OFF+56]), "+f"(d[OFF+57]), "+f"(d[OFF+58]), "+f"(d[OFF+59]), "+f"(d[OFF+60]), "+f"(d[OFF+61]), "+f"(d[OFF+62]), "+f"(d[OFF+63]),
      "+f"(d[OFF+64]), "+f"(d[OFF+65]), "+f"(d[OFF+66]), "+f"(d[OFF+67]), "+f"(d[OFF+68]), "+f"(d[OFF+69]), "+f"(d[OFF+70]), "+f"(d[OFF+71]),
      "+f"(d[OFF+72]), "+f"(d[OFF+73]), "+f"(d[OFF+74]), "+f"(d[OFF+75]), "+f"(d[OFF+76]), "+f"(d[OFF+77]), "+f"(d[OFF+78]), "+f"(d[OFF+79]),
      "+f"(d[OFF+80]), "+f"(d[OFF+81]), "+f"(d[OFF+82]), "+f"(d[OFF+83]), "+f"(d[OFF+84]), "+f"(d[OFF+85]), "+f"(d[OFF+86]), "+f"(d[OFF+87]),
      "+f"(d[OFF+88]), "+f"(d[OFF+89]), "+f"(d[OFF+90]), "+f"(d[OFF+91]), "+f"(d[OFF+92]), "+f"(d[OFF+93]), "+f"(d[OFF+94]), "+f"(d[OFF+95]),
      "+f"(d[OFF+96]), "+f"(d[OFF+97]), "+f"(d[OFF+98]), "+f"(d[OFF+99]), "+f"(d[OFF+100]), "+f"(d[OFF+101]), "+f"(d[OFF+102]), "+f"(d[OFF+103]),
      "+f"(d[OFF+104]), "+f"(d[OFF+105]), "+f"(d[OFF+106]), "+f"(d[OFF+107]), "+f"(d[OFF+108]), "+f"(d[OFF+109]), "+f"(d[OFF+110]), "+f"(d[OFF+111])
      : "l"(da), "l"(db), "r"(scale_d));
}

__device__ __forceinline__ uint32_t smem_u32(const void* p) { return (uint32_t)__cvta_generic_to_shared(p); }
__device__ __forceinline__ void mbar_init(uint32_t bar, uint32_t cnt) {
  asm volatile("mbarrier.init.shared::cta.b64 [%0], %1;" ::"r"(bar), "r"(cnt) : "memory");
}
__device__ __forceinline__ void mbar_expect_tx(uint32_t bar, uint32_t bytes) {
  asm volatile("mbarrier.arrive.expect_tx.shared::cta.b64 _, [%0], %1;" ::"r"(bar), "r"(bytes) : "memory");
}
__device__ __forceinline__ void mbar_arrive(uint32_t bar) {
  asm volatile("mbarrier.arrive.shared::cta.b64 _, [%0];" ::"r"(bar) : "memory");
}
__device__ __forceinline__ void mbar_arrive_remote(uint32_t cluster_addr) {
  asm volatile("mbarrier.arrive.shared::cluster.b64 _, [%0];" ::"r"(cluster_addr) : "memory");
}
__device__ __forceinline__ bool mbar_test(uint32_t bar, uint32_t parity) {
  uint32_t ok;
  asm volatile("{\n.reg .pred p;\nmbarrier.test_wait.parity.shared::cta.b64 p, [%1], %2;\nselp.u32 %0, 1, 0, p;\n}"
               : "=r"(ok) : "r"(bar), "r"(parity) : "memory");
  return ok;
}
__device__ __forceinline__ void mbar_wait(uint32_t bar, uint32_t parity) {
  asm volatile(
      "{\n.reg .pred p;\n.reg .u32 n;\nmov.u32 n, 0;\n"
      "LAB_WAIT:\nmbarrier.try_wait.parity.shared::cta.b64 p, [%0], %1;\n@p bra LAB_DONE;\n"
      "add.u32 n, n, 1;\nsetp.lt.u32 p, n, 1048576;\n@p bra LAB_WAIT;\ntrap;\nLAB_DONE:\n}" ::"r"(bar), "r"(parity) : "memory");
}
__device__ __forceinline__ void bulk_load(uint32_t dst, const void* src, uint32_t bytes, uint32_t bar) {
  asm volatile("cp.async.bulk.shared::cluster.global.mbarrier::complete_tx::bytes [%0], [%1], %2, [%3];"
               ::"r"(dst), "l"(src), "r"(bytes), "r"(bar) : "memory");
}
__device__ __forceinline__ void tma_store_2d(const CUtensorMap* m, uint32_t src, int c0, int c1, uint64_t pol) {
  asm volatile("cp.async.bulk.tensor.2d.global.shared::cta.bulk_group.L2::cache_hint [%0, {%2, %3}], [%1], %4;"
               ::"l"(m), "r"(src), "r"(c0), "r"(c1), "l"(pol) : "memory");
}
__device__ __forceinline__ void tma_store_2d_elect(const CUtensorMap* m, uint32_t src, int c0, int c1, uint64_t pol) {
  asm volatile("{\n.reg .pred p;\nelect.sync _|p, 0xffffffff;\n"
               "@p cp.async.bulk.tensor.2d.global.shared::cta.bulk_group.L2::cache_hint [%0, {%2, %3}], [%1], %4;\n"
               "@p cp.async.bulk.commit_group;\n}"
               ::"l"(m), "r"(src), "r"(c0), "r"(c1), "l"(pol) : "memory");
}
__device__ __forceinline__ void bulk_commit() { asm volatile("cp.async.bulk.commit_group;" ::: "memory"); }
template <int NG> __device__ __forceinline__ void bulk_wait_read() { asm volatile("cp.async.bulk.wait_group.read %0;" ::"n"(NG) : "memory"); }
__device__ __forceinline__ void fence_async_smem() { asm volatile("fence.proxy.async.shared::cta;" ::: "memory"); }
__device__ __forceinline__ void wg_fence() { asm volatile("wgmma.fence.sync.aligned;" ::: "memory"); }
__device__ __forceinline__ void wg_commit() { asm volatile("wgmma.commit_group.sync.aligned;" ::: "memory"); }
template <int NG> __device__ __forceinline__ void wg_wait() { asm volatile("wgmma.wait_group.sync.aligned %0;" ::"n"(NG) : "memory"); }
__device__ __forceinline__ void cluster_arrive() { asm volatile("barrier.cluster.arrive.relaxed.aligned;" ::: "memory"); }
__device__ __forceinline__ void cluster_wait() { asm volatile("barrier.cluster.wait.aligned;" ::: "memory"); }
template <int R> __device__ __forceinline__ void reg_inc() { asm volatile("setmaxnreg.inc.sync.aligned.u32 %0;" ::"n"(R)); }
template <int R> __device__ __forceinline__ void reg_dec() { asm volatile("setmaxnreg.dec.sync.aligned.u32 %0;" ::"n"(R)); }
__device__ __forceinline__ void wg_sync(int wg) {
  if (wg == 0) asm volatile("bar.sync 1, 128;" ::: "memory"); else asm volatile("bar.sync 2, 128;" ::: "memory");
}
__device__ __forceinline__ uint32_t mapa(uint32_t a, uint32_t cta) {
  uint32_t r; asm("mapa.shared::cluster.u32 %0, %1, %2;" : "=r"(r) : "r"(a), "r"(cta)); return r;
}
__device__ __forceinline__ uint64_t make_desc(uint32_t addr, uint32_t lbo, uint32_t sbo, uint32_t mode) {
  return (uint64_t)((addr & 0x3FFFF) >> 4) | ((uint64_t)(lbo >> 4) << 16) | ((uint64_t)(sbo >> 4) << 32) | ((uint64_t)mode << 62);
}
__device__ __forceinline__ uint32_t pack_bf16(float lo, float hi) {
  uint32_t r; asm("cvt.rn.bf16x2.f32 %0, %1, %2;" : "=r"(r) : "f"(hi), "f"(lo)); return r;
}
__device__ __forceinline__ void stmatrix_x4(uint32_t addr, uint32_t a, uint32_t b, uint32_t c, uint32_t d) {
  asm volatile("stmatrix.sync.aligned.m8n8.x4.shared.b16 [%0], {%1,%2,%3,%4};" ::"r"(addr), "r"(a), "r"(b), "r"(c), "r"(d) : "memory");
}
__device__ __forceinline__ void prefetch_l2(const void* p) { asm volatile("prefetch.global.L2 [%0];" ::"l"(p) : "memory"); }
__device__ __forceinline__ void wait_clock(uint32_t t0, int d) { while ((int)((uint32_t)clock() - t0) < d) {} }
__device__ __forceinline__ void stg64(unsigned char* p, uint2 v) {
  asm volatile("st.global.v2.u32 [%0], {%1,%2};" ::"l"(p), "r"(v.x), "r"(v.y) : "memory");
}
__device__ __forceinline__ uint2 lds64(uint32_t a) {
  uint2 r; asm volatile("ld.shared.v2.u32 {%0,%1}, [%2];" : "=r"(r.x), "=r"(r.y) : "r"(a) : "memory"); return r;
}
__device__ __forceinline__ uint4 lds128(uint32_t a) {
  uint4 r; asm volatile("ld.shared.v4.u32 {%0,%1,%2,%3}, [%4];" : "=r"(r.x), "=r"(r.y), "=r"(r.z), "=r"(r.w) : "r"(a) : "memory"); return r;
}

template <bool ARM, bool X, bool W>
__device__ __forceinline__ void issue_stage(uint32_t bar, uint32_t xdst, const CUtensorMap* m, int c0, int c1,
                                            uint32_t wdst, const void* wsrc) {
  asm volatile("{\n.reg .pred p, px, pw, pa;\nelect.sync _|p, 0xffffffff;\n"
               "setp.ne.and.u32 pa, %7, 0, p;\nsetp.ne.and.u32 px, %8, 0, p;\nsetp.ne.and.u32 pw, %9, 0, p;\n"
               "@pa mbarrier.arrive.expect_tx.shared::cta.b64 _, [%0], %10;\n"
               "@pw cp.async.bulk.shared::cluster.global.mbarrier::complete_tx::bytes.multicast::cluster [%5], [%6], %11, [%0], %12;\n"
               "@px cp.async.bulk.tensor.2d.shared::cluster.global.mbarrier::complete_tx::bytes [%1], [%2, {%3, %4}], [%0];\n}"
               ::"r"(bar), "r"(xdst), "l"(m), "r"(c0), "r"(c1), "r"(wdst), "l"(wsrc), "n"((int)ARM), "n"((int)X), "n"((int)W),
                 "n"(STB), "n"(WH), "h"((uint16_t)3) : "memory");
}

struct Lut { uint32_t lo[4], hi[4], m4, id; };
__device__ __forceinline__ uint32_t prmt(uint32_t a, uint32_t b, uint32_t s) {
  uint32_t r; asm("prmt.b32 %0, %1, %2, %3;" : "=r"(r) : "r"(a), "r"(b), "r"(s)); return r;
}
__device__ __forceinline__ Lut make_lut(uint4 c0, uint4 c1) {
  Lut l;
  l.lo[0] = prmt(c0.x, c0.y, 0x6420); l.hi[0] = prmt(c0.x, c0.y, 0x7531);
  l.lo[1] = prmt(c0.z, c0.w, 0x6420); l.hi[1] = prmt(c0.z, c0.w, 0x7531);
  l.lo[2] = prmt(c1.x, c1.y, 0x6420); l.hi[2] = prmt(c1.x, c1.y, 0x7531);
  l.lo[3] = prmt(c1.z, c1.w, 0x6420); l.hi[3] = prmt(c1.z, c1.w, 0x7531);
  l.m4 = 0x4444; l.id = 0x3210;
  return l;
}
__device__ __forceinline__ uint2 dequant4(int4 v, const Lut& l, uint2 s) {
  const uint32_t sel = (uint32_t)(v.x + v.y * 16) + (uint32_t)(v.z + v.w * 16) * 256;
  const uint32_t s7 = sel & 0x7777;
  uint32_t s2;
  asm("lop3.b32 %0, %1, %2, %3, 0xEA;" : "=r"(s2) : "r"(sel >> 1), "r"(l.m4), "r"(l.id));
  const uint32_t lo = prmt(prmt(l.lo[0], l.lo[1], s7), prmt(l.lo[2], l.lo[3], s7), s2);
  const uint32_t hi = prmt(prmt(l.hi[0], l.hi[1], s7), prmt(l.hi[2], l.hi[3], s7), s2);
  uint2 r;
  asm("mul.rn.bf16x2 %0, %1, %2;" : "=r"(r.x) : "r"(prmt(lo, hi, 0x5140)), "r"(s.x));
  asm("mul.rn.bf16x2 %0, %1, %2;" : "=r"(r.y) : "r"(prmt(lo, hi, 0x7362)), "r"(s.y));
  return r;
}

template <int B0, int B1>
__device__ __forceinline__ void stage_boxes(const uint32_t (&pk)[56], uint32_t buf, int warp, int lane) {
  const int r = warp * 16 + (lane & 15), ch = lane >> 4;
#pragma unroll
  for (int b = B0; b < B1; b++) {
#pragma unroll
    for (int p = 0; p < 2; p++) {
      const int cc = p * 2 + ch;
      stmatrix_x4(buf + (b - B0) * 4096 + r * 64 + ((cc ^ ((r >> 1) & 3)) << 4),
                  pk[b * 8 + p * 4], pk[b * 8 + p * 4 + 1], pk[b * 8 + p * 4 + 2], pk[b * 8 + p * 4 + 3]);
    }
  }
}

__global__ void __cluster_dims__(2, 1, 1) __launch_bounds__(384, 1)
nf4_gemm_kernel(const int* __restrict__ q, const __nv_bfloat16* __restrict__ cb, const __nv_bfloat16* __restrict__ am,
                unsigned char* __restrict__ gw, const __nv_bfloat16* __restrict__ x,
                const __grid_constant__ TensorMaps maps) {
  const CUtensorMap& mx = maps.x;
  const CUtensorMap& mo = maps.out;
  extern __shared__ __align__(1024) unsigned char smem_raw[];
  const uint32_t sb = smem_u32(smem_raw);
  const uint32_t epi = sb + STAGES * STB, bars = epi + EPI;
  const uint32_t cst = bars + 512, cfull = bars + 192;
  auto full = [&](int s) { return bars + s * 8; };
  auto empty = [&](int s) { return bars + 32 + s * 8; };
  auto jdone = [&](int j) { return bars + 64 + j * 8; };
  unsigned int* gflag = (unsigned int*)(gw + (size_t)K * N * 2);
  unsigned int* gepoch = gflag + 256;

  const int c = blockIdx.x, wid = threadIdx.x >> 5, wg = wid >> 2, lane = threadIdx.x & 31, rank = c & 1;
  const int jc = c >> 1, b7 = jc - 36, k7 = (b7 * 37) >> 8;
  const int gidx = jc < 4 ? 15 : jc < 36 ? ((jc - 4) & 7) : 8 + b7 - 7 * k7;
  const int kidx = jc < 4 ? jc : jc < 36 ? ((jc - 4) >> 3) : k7;
  const int mt = (gidx & 7) * 2 + rank, pj = 4 * (gidx >> 3) + kidx;

  const int grp = mt & 3, r0 = (mt >> 2) * 16 + (lane >> 3);
  const int col = pj * BN + wid * 32 + (lane & 7) * 4;
  const uint32_t cstart = clock();
  wait_clock(cstart, grp * T_JOB0_STEP);
  int4 v[4]; uint4 cb0, cb1; uint2 sc0;
  asm volatile("{\n.reg .pred p;\nsetp.lt.s32 p, %30, 7;\n"
               "@p ld.global.nc.L1::no_allocate.L2::cache_hint.v4.s32 {%0,%1,%2,%3}, [%26], %29;\n"
               "@p ld.global.nc.L1::no_allocate.L2::cache_hint.v4.s32 {%4,%5,%6,%7}, [%26+57344], %29;\n"
               "@p ld.global.nc.L1::no_allocate.L2::cache_hint.v4.s32 {%8,%9,%10,%11}, [%26+114688], %29;\n"
               "@p ld.global.nc.L1::no_allocate.L2::cache_hint.v4.s32 {%12,%13,%14,%15}, [%26+172032], %29;\n"
               "@p ld.global.nc.v4.u32 {%16,%17,%18,%19}, [%27];\n@p ld.global.nc.v4.u32 {%20,%21,%22,%23}, [%27+16];\n"
               "@p ld.global.nc.v2.u32 {%24,%25}, [%28];\n}"
               : "=r"(v[0].x), "=r"(v[0].y), "=r"(v[0].z), "=r"(v[0].w), "=r"(v[1].x), "=r"(v[1].y), "=r"(v[1].z), "=r"(v[1].w),
                 "=r"(v[2].x), "=r"(v[2].y), "=r"(v[2].z), "=r"(v[2].w), "=r"(v[3].x), "=r"(v[3].y), "=r"(v[3].z), "=r"(v[3].w),
                 "=r"(cb0.x), "=r"(cb0.y), "=r"(cb0.z), "=r"(cb0.w), "=r"(cb1.x), "=r"(cb1.y), "=r"(cb1.z), "=r"(cb1.w),
                 "=r"(sc0.x), "=r"(sc0.y)
               : "l"(q + (grp * 64 + r0) * N + col), "l"(cb), "l"(am + col), "l"(EVICT_FIRST), "r"(wid));
  if (threadIdx.x == 288) {
    mbar_init(cfull, 1);
    fence_async_smem();
  } else if (threadIdx.x == 256) {
#pragma unroll
    for (int s = 0; s < STAGES; s++) { mbar_init(full(s), 1); mbar_init(empty(s), 4); }
    asm volatile("fence.mbarrier_init.release.cluster;" ::: "memory");
    fence_async_smem();
  } else if (threadIdx.x == 320) {
#pragma unroll
    for (int j = 0; j < 8; j++) mbar_init(jdone(j), j == 0 ? 7 : 2);
  }
  __syncthreads();
  cluster_arrive();
  const int lo4 = (lane >> 3) * 64 + ((((lane & 7) >> 1) ^ (lane >> 4)) << 4) + (lane & 1) * 8;
  const int hi4 = (lo4 ^ 32) + 256;

  if (wg == 2) {
    reg_dec<REG_SIDE>();
    const int w = __shfl_sync(~0u, wid & 3, 0);
    if (w >= 2) {
      const __nv_bfloat16* xq = x + (size_t)(mt * BM + pj * 16 + (lane & 15)) * K;
      for (int i = w - 2; i < 4; i += 2) { wait_clock(cstart, T_XPF0 + i * T_XPF); if (lane < 16) prefetch_l2(xq + i * BK); }
      mbar_wait(cfull, 0);
      const Lut lut = make_lut(lds128(cst), lds128(cst + 16));
      uint2 sc[7];
#pragma unroll
      for (int g = 0; g < 7; g++) sc[g] = lds64(cst + 32 + g * 64 + (lane & 7) * 8);
      const int rw = r0 + (w - 2) * 8;
#pragma unroll 1
      for (int j = 1; j < 8; j++) {
        const int i = 4 * j + grp;
        wait_clock(cstart, j == 1 ? T_JOB1 + grp * T_JOB1_STEP : T_JOB2 + (i - 8) * T_BLOCK);
        const int* p = q + (size_t)((i & 15) * 64 + rw) * N + (pj + (i >> 4) * 8) * BN + (lane & 7) * 4;
        int4 u[14];
#pragma unroll
        for (int g = 0; g < 14; g++)
          asm volatile("ld.global.nc.L1::no_allocate.L2::cache_hint.v4.s32 {%0,%1,%2,%3}, [%4], %5;"
                       : "=r"(u[g].x), "=r"(u[g].y), "=r"(u[g].z), "=r"(u[g].w)
                       : "l"(p + (size_t)(g / 7) * 4 * N + (g % 7) * 32), "l"(EVICT_FIRST));
        if (j == 4) {
#pragma unroll
          for (int g = 0; g < 7; g++) sc[g] = lds64(cst + 480 + g * 64 + (lane & 7) * 8);
        }
        unsigned char* blk = gw + ((size_t)(pj + (i >> 4) * 8) * KB + (i & 15)) * WB + ((mt >> 2) * 2 + w - 2) * 3584;
#pragma unroll
        for (int g = 0; g < 14; g++)
          *(uint2*)(blk + (g < 7 ? lo4 : hi4) + (g % 7) * 512) = dequant4(u[g], lut, sc[g % 7]);
        __syncwarp();
        if (lane == 0) mbar_arrive(jdone(j));
      }
      cluster_wait();
    } else if (w == 1) {
      if (lane == 0) {
        mbar_expect_tx(cfull, 32 + 2 * 448);
        bulk_load(cst, cb, 32, cfull);
        bulk_load(cst + 32, am + pj * BN, 448, cfull);
        bulk_load(cst + 480, am + (pj + 8) * BN, 448, cfull);
      }
#pragma unroll 1
      for (int j = 0; j < 8; j++) {
        mbar_wait(jdone(j), 0);
        if (lane == 0) asm volatile("red.release.gpu.global.add.u32 [%0], 1;" ::"l"(gflag + pj * 32 + 4 * j + grp) : "memory");
        __syncwarp();
      }
      cluster_wait();
    } else {
      if (lane == 0) asm volatile("prefetch.tensormap [%0];" ::"l"(&mx) : "memory");
      const unsigned int epoch = gepoch[c];
      const unsigned int* fl = gflag + pj * 32 + lane;
      const __nv_bfloat16* xp = x + (size_t)(mt * BM + pj * 16 + (lane & 15)) * K;
      cluster_wait();
      const unsigned int target = (epoch + 1) * 4;
      unsigned int ready = 0;
      int s = 0, ph = 1;
      const unsigned char* wsrc = gw + (size_t)pj * KB * WB + rank * WH;
      auto poll = [&]() {
        unsigned int f;
        asm volatile("ld.relaxed.gpu.global.u32 %0, [%1];" : "=r"(f) : "l"(fl) : "memory");
        return __ballot_sync(~0u, (int)(f - target) >= 0);
      };
      auto acquire = [&]() {
        asm volatile("fence.acquire.gpu;" ::: "memory");
        __syncwarp();
        asm volatile("fence.proxy.async.global;" ::: "memory");
      };
#pragma unroll 1
      for (int i = 0; i < NBLK; i++) {
        const uint32_t xs = sb + s * STB, ws = xs + XB + rank * WH, fb = full(s);
        const int kc = (i & 15) * BK;
        for (int n = 0; n < (1 << 22) && !((ready >> i) & 1) && !mbar_test(empty(s), ph); n++) {
          const unsigned int r = poll();
          if ((r >> i) & 1) { acquire(); ready = r; }
        }
        if ((ready >> i) & 1) {
          if (i == 2 || i == 3) mbar_wait(full(i - 2), 0);
          mbar_wait(empty(s), ph);
          issue_stage<true, true, true>(fb, xs, &mx, kc, mt * BM, ws, wsrc);
        } else {
          mbar_wait(empty(s), ph);
          if (i >= 4) issue_stage<true, true, false>(fb, xs, &mx, kc, mt * BM, ws, wsrc);
          int spins = 0;
          do {
            ready = poll();
            if (++spins > (1 << 22)) asm volatile("trap;");
          } while (!((ready >> i) & 1));
          acquire();
          if (i >= 4) {
            issue_stage<false, false, true>(fb, xs, &mx, kc, mt * BM, ws, wsrc);
          } else {
            if (i >= 2) mbar_wait(full(i - 2), 0);
            issue_stage<true, true, true>(fb, xs, &mx, kc, mt * BM, ws, wsrc);
          }
        }
        if (i + 4 < KB && lane < 16) prefetch_l2(xp + (i + 4) * BK);
        wsrc += (i == KB - 1) ? (size_t)(7 * KB + 1) * WB : (size_t)WB;
        if (++s == STAGES) { s = 0; ph ^= 1; }
      }
      if (lane == 0) gepoch[c] = epoch + 1;
    }
  } else {
    const int widu = __shfl_sync(~0u, wid, 0), warp = widu & 3, wgu = widu >> 2;
    unsigned char* j0lo = gw + (size_t)(pj * KB + grp) * WB + (mt >> 2) * 7168 + wid * 512 + lo4;
    unsigned char* j0hi = j0lo + (hi4 - lo4);
    asm volatile("" : "+l"(j0lo), "+l"(j0hi));
    if (wid < 7) {
      const Lut lut = make_lut(cb0, cb1);
#pragma unroll
      for (int g = 0; g < 4; g++) stg64(((g & 1) ? j0hi : j0lo) + (g >> 1) * 3584, dequant4(v[g], lut, sc0));
      __syncwarp();
      if (lane == 0) mbar_arrive(jdone(0));
    }
    reg_inc<REG_CONSUMER>();
    const bool leader = (threadIdx.x & 127) == 0;
    if (leader) asm volatile("prefetch.tensormap [%0];" ::"l"(&mo) : "memory");
    float acc[112];
    const uint32_t empty_peer = mapa(empty(0), rank ^ 1);
    cluster_wait();
    int s = 0, ph = 0;
    const uint64_t da0 = make_desc(sb + wgu * 8192, 16, 1024, 1), db0 = make_desc(sb + XB, 512, 3584, 2);
    auto mma_block = [&](int first) {
      uint64_t da = da0 + s * (STB >> 4), db = db0 + s * (STB >> 4);
      asm volatile("" : "+l"(da), "+l"(db));
      mbar_wait(full(s), ph);
      wg_fence();
#pragma unroll
      for (int k = 0; k < 4; k++) wgmma_n224<0>(acc, da + k * 2, db + k * 448, !(first && k == 0));
      wg_commit();
    };
    auto release_prev = [&]() {
      const int st = s == 0 ? STAGES - 1 : s - 1;
      if (leader) { mbar_arrive(empty(st)); mbar_arrive_remote(empty_peer + st * 8); }
    };
    auto advance = [&]() { if (++s == STAGES) { s = 0; ph ^= 1; } };

#pragma unroll 1
    for (int kb = 0; kb < KB; kb++) {
      mma_block(kb == 0);
      wg_wait<1>();
      if (kb > 0) release_prev();
      advance();
    }
    wg_wait<0>();
    release_prev();
    uint32_t pk[56];
#pragma unroll
    for (int i = 0; i < 56; i++) pk[i] = pack_bf16(acc[2 * i], acc[2 * i + 1]);

    const uint32_t ebuf = epi + wgu * 24576;
    const int row0 = mt * BM + wgu * 64, col0 = pj * BN, col1 = (pj + 8) * BN;
#pragma unroll
    for (int kb = 0; kb < 7; kb++) {
      mma_block(kb == 0);
      if (kb > 0) { wg_wait<1>(); release_prev(); }
      advance();
      if (kb == 6) { if (leader) bulk_wait_read<5>(); wg_sync(wgu); }
      const uint32_t buf = ebuf + (kb % 6) * 4096;
      if (kb == 0) stage_boxes<0, 1>(pk, buf, warp, lane);
      if (kb == 1) stage_boxes<1, 2>(pk, buf, warp, lane);
      if (kb == 2) stage_boxes<2, 3>(pk, buf, warp, lane);
      if (kb == 3) stage_boxes<3, 4>(pk, buf, warp, lane);
      if (kb == 4) stage_boxes<4, 5>(pk, buf, warp, lane);
      if (kb == 5) stage_boxes<5, 6>(pk, buf, warp, lane);
      if (kb == 6) stage_boxes<6, 7>(pk, buf, warp, lane);
      fence_async_smem();
      wg_sync(wgu);
      if (leader) { tma_store_2d(&mo, buf, col0 + kb * 32, row0, EVICT_FIRST); bulk_commit(); }
    }
#pragma unroll 1
    for (int kb = 7; kb < KB; kb++) {
      const bool hold = kb == KB - 4 && wgu == 1;
      if (hold) { wg_wait<0>(); release_prev(); asm volatile("bar.sync 4, 256;" ::: "memory"); }
      mma_block(0);
      wg_wait<1>();
      if (kb <= KB - 4 && !hold) release_prev();
      if (kb == 10 && leader) bulk_wait_read<0>();
      if (kb == KB - 1 && wgu == 0) asm volatile("bar.arrive 4, 256;" ::: "memory");
      advance();
    }
    wg_wait<0>();
    auto box_buf = [&](int b) { return b < 6 ? ebuf + b * 4096 : sb + wgu * 8192; };
#pragma unroll
    for (int b = 0; b < 7; b++) {
#pragma unroll
      for (int i = b * 8; i < b * 8 + 8; i++) pk[i] = pack_bf16(acc[2 * i], acc[2 * i + 1]);
      const int r = warp * 16 + (lane & 15), ch = lane >> 4;
#pragma unroll
      for (int p = 0; p < 2; p++)
        stmatrix_x4(box_buf(b) + r * 64 + (((p * 2 + ch) ^ ((r >> 1) & 3)) << 4),
                    pk[b * 8 + p * 4], pk[b * 8 + p * 4 + 1], pk[b * 8 + p * 4 + 2], pk[b * 8 + p * 4 + 3]);
      if (b == 1 || b == 3 || b == 6) {
        fence_async_smem();
        wg_sync(wgu);
        const int b0 = b == 1 ? 0 : b == 3 ? 2 : 4;
        if (warp <= b - b0) tma_store_2d_elect(&mo, box_buf(b0 + warp), col1 + (b0 + warp) * 32, row0, EVICT_FIRST);
      }
    }
    bulk_wait_read<0>();
  }
}

typedef CUresult (*EncodeTiledFn)(CUtensorMap*, CUtensorMapDataType, cuuint32_t, void*, const cuuint64_t*, const cuuint64_t*,
                                  const cuuint32_t*, const cuuint32_t*, CUtensorMapInterleave, CUtensorMapSwizzle,
                                  CUtensorMapL2promotion, CUtensorMapFloatOOBfill);

void make_map_2d(EncodeTiledFn enc, CUtensorMap* m, void* base, uint64_t inner, uint64_t outer, uint32_t b0, uint32_t b1,
                 CUtensorMapSwizzle sw, CUtensorMapL2promotion prom) {
  cuuint64_t dims[2] = {inner, outer};
  cuuint64_t strides[1] = {inner * 2};
  cuuint32_t box[2] = {b0, b1};
  cuuint32_t es[2] = {1, 1};
  enc(m, CU_TENSOR_MAP_DATA_TYPE_BFLOAT16, 2, base, dims, strides, box, es, CU_TENSOR_MAP_INTERLEAVE_NONE, sw, prom,
      CU_TENSOR_MAP_FLOAT_OOB_FILL_NONE);
}

}

extern "C" void kernel_launch(void* const* d_in, const int* in_sizes, int n_in, void* d_out, int out_size) {
  (void)in_sizes; (void)n_in; (void)out_size;
  static EncodeTiledFn enc = nullptr;
  static void* scratch = nullptr;
  if (!enc) {
    void* f = nullptr;
    cudaDriverEntryPointQueryResult qr;
    cudaGetDriverEntryPoint("cuTensorMapEncodeTiled", &f, cudaEnableDefault, &qr);
    enc = (EncodeTiledFn)f;
    cudaFuncSetAttribute(nf4_gemm_kernel, cudaFuncAttributeMaxDynamicSharedMemorySize, SMEM);
    cudaGetSymbolAddress(&scratch, g_scratch);
  }
  TensorMaps maps;
  make_map_2d(enc, &maps.x, d_in[0], K, M, BK, BM, CU_TENSOR_MAP_SWIZZLE_128B, CU_TENSOR_MAP_L2_PROMOTION_L2_128B);
  make_map_2d(enc, &maps.out, d_out, N, M, 32, 64, CU_TENSOR_MAP_SWIZZLE_64B, CU_TENSOR_MAP_L2_PROMOTION_NONE);
  nf4_gemm_kernel<<<128, 384, SMEM, cudaStreamPerThread>>>(
      (const int*)d_in[1], (const __nv_bfloat16*)d_in[2], (const __nv_bfloat16*)d_in[3], (unsigned char*)scratch,
      (const __nv_bfloat16*)d_in[0], maps);
}
```

```cpp
#include <cuda_runtime.h>
#include <cuda_bf16.h>
#include <cuda.h>
#include <stdint.h>

namespace {

constexpr int M = 2048, N = 3584, K = 1024;
constexpr int BM = 128, BN = 224, BK = 64, KB = K / BK, STAGES = 4, NBLK = 2 * KB;
constexpr int XB = BM * BK * 2, WB = BN * BK * 2, STB = XB + WB, WH = WB / 2;
constexpr int EPI = 49152;
constexpr int SMEM = STAGES * STB + EPI + 512 + 1024;
constexpr int REG_CONSUMER = 200, REG_SIDE = 104;
constexpr int T_JOB0_STEP = 300, T_XPF0 = 1400, T_XPF = 200, T_JOB1 = 2600, T_JOB1_STEP = 350, T_JOB2 = 4200, T_BLOCK = 700;
constexpr uint64_t EVICT_FIRST = 0x12F0000000000000ull;

struct alignas(128) TensorMaps { CUtensorMap x, out; };

__device__ __align__(1024) unsigned char g_scratch[(size_t)K * N * 2 + 2048];

__device__ __forceinline__ void wgmma_n224(float (&d)[112], uint64_t da, uint64_t db, int scale_d) {
  asm volatile("{\n.reg .pred p;\nsetp.ne.b32 p, %114, 0;\n"
      "wgmma.mma_async.sync.aligned.m64n224k16.f32.bf16.bf16 {"
      "%0, %1, %2, %3, %4, %5, %6, %7, %8, %9, %10, %11, %12, %13, %14, %15, "
      "%16, %17, %18, %19, %20, %21, %22, %23, %24, %25, %26, %27, %28, %29, %30, %31, "
      "%32, %33, %34, %35, %36, %37, %38, %39, %40, %41, %42, %43, %44, %45, %46, %47, "
      "%48, %49, %50, %51, %52, %53, %54, %55, %56, %57, %58, %59, %60, %61, %62, %63, "
      "%64, %65, %66, %67, %68, %69, %70, %71, %72, %73, %74, %75, %76, %77, %78, %79, "
      "%80, %81, %82, %83, %84, %85, %86, %87, %88, %89, %90, %91, %92, %93, %94, %95, "
      "%96, %97, %98, %99, %100, %101, %102, %103, %104, %105, %106, %107, %108, %109, %110, %111"
      "}, %112, %113, p, 1, 1, 0, 1;\n}\n"
      : "+f"(d[0]), "+f"(d[1]), "+f"(d[2]), "+f"(d[3]), "+f"(d[4]), "+f"(d[5]), "+f"(d[6]), "+f"(d[7]),
      "+f"(d[8]), "+f"(d[9]), "+f"(d[10]), "+f"(d[11]), "+f"(d[12]), "+f"(d[13]), "+f"(d[14]), "+f"(d[15]),
      "+f"(d[16]), "+f"(d[17]), "+f"(d[18]), "+f"(d[19]), "+f"(d[20]), "+f"(d[21]), "+f"(d[22]), "+f"(d[23]),
      "+f"(d[24]), "+f"(d[25]), "+f"(d[26]), "+f"(d[27]), "+f"(d[28]), "+f"(d[29]), "+f"(d[30]), "+f"(d[31]),
      "+f"(d[32]), "+f"(d[33]), "+f"(d[34]), "+f"(d[35]), "+f"(d[36]), "+f"(d[37]), "+f"(d[38]), "+f"(d[39]),
      "+f"(d[40]), "+f"(d[41]), "+f"(d[42]), "+f"(d[43]), "+f"(d[44]), "+f"(d[45]), "+f"(d[46]), "+f"(d[47]),
      "+f"(d[48]), "+f"(d[49]), "+f"(d[50]), "+f"(d[51]), "+f"(d[52]), "+f"(d[53]), "+f"(d[54]), "+f"(d[55]),
      "+f"(d[56]), "+f"(d[57]), "+f"(d[58]), "+f"(d[59]), "+f"(d[60]), "+f"(d[61]), "+f"(d[62]), "+f"(d[63]),
      "+f"(d[64]), "+f"(d[65]), "+f"(d[66]), "+f"(d[67]), "+f"(d[68]), "+f"(d[69]), "+f"(d[70]), "+f"(d[71]),
      "+f"(d[72]), "+f"(d[73]), "+f"(d[74]), "+f"(d[75]), "+f"(d[76]), "+f"(d[77]), "+f"(d[78]), "+f"(d[79]),
      "+f"(d[80]), "+f"(d[81]), "+f"(d[82]), "+f"(d[83]), "+f"(d[84]), "+f"(d[85]), "+f"(d[86]), "+f"(d[87]),
      "+f"(d[88]), "+f"(d[89]), "+f"(d[90]), "+f"(d[91]), "+f"(d[92]), "+f"(d[93]), "+f"(d[94]), "+f"(d[95]),
      "+f"(d[96]), "+f"(d[97]), "+f"(d[98]), "+f"(d[99]), "+f"(d[100]), "+f"(d[101]), "+f"(d[102]), "+f"(d[103]),
      "+f"(d[104]), "+f"(d[105]), "+f"(d[106]), "+f"(d[107]), "+f"(d[108]), "+f"(d[109]), "+f"(d[110]), "+f"(d[111])
      : "l"(da), "l"(db), "r"(scale_d));
}

__device__ __forceinline__ uint32_t smem_u32(const void* p) { return (uint32_t)__cvta_generic_to_shared(p); }
__device__ __forceinline__ void mbar_init(uint32_t bar, uint32_t cnt) {
  asm volatile("mbarrier.init.shared::cta.b64 [%0], %1;" ::"r"(bar), "r"(cnt) : "memory");
}
__device__ __forceinline__ void mbar_expect_tx(uint32_t bar, uint32_t bytes) {
  asm volatile("mbarrier.arrive.expect_tx.shared::cta.b64 _, [%0], %1;" ::"r"(bar), "r"(bytes) : "memory");
}
__device__ __forceinline__ void mbar_arrive(uint32_t bar) {
  asm volatile("mbarrier.arrive.shared::cta.b64 _, [%0];" ::"r"(bar) : "memory");
}
__device__ __forceinline__ void mbar_arrive_remote(uint32_t cluster_addr) {
  asm volatile("mbarrier.arrive.shared::cluster.b64 _, [%0];" ::"r"(cluster_addr) : "memory");
}
__device__ __forceinline__ bool mbar_test(uint32_t bar, uint32_t parity) {
  uint32_t ok;
  asm volatile("{\n.reg .pred p;\nmbarrier.test_wait.parity.shared::cta.b64 p, [%1], %2;\nselp.u32 %0, 1, 0, p;\n}"
               : "=r"(ok) : "r"(bar), "r"(parity) : "memory");
  return ok;
}
__device__ __forceinline__ void mbar_wait(uint32_t bar, uint32_t parity) {
  asm volatile(
      "{\n.reg .pred p;\n.reg .u32 n;\nmov.u32 n, 0;\n"
      "LAB_WAIT:\nmbarrier.try_wait.parity.shared::cta.b64 p, [%0], %1;\n@p bra LAB_DONE;\n"
      "add.u32 n, n, 1;\nsetp.lt.u32 p, n, 1048576;\n@p bra LAB_WAIT;\ntrap;\nLAB_DONE:\n}" ::"r"(bar), "r"(parity) : "memory");
}
__device__ __forceinline__ void bulk_load(uint32_t dst, const void* src, uint32_t bytes, uint32_t bar) {
  asm volatile("cp.async.bulk.shared::cluster.global.mbarrier::complete_tx::bytes [%0], [%1], %2, [%3];"
               ::"r"(dst), "l"(src), "r"(bytes), "r"(bar) : "memory");
}
__device__ __forceinline__ void tma_store_2d(const CUtensorMap* m, uint32_t src, int c0, int c1, uint64_t pol) {
  asm volatile("cp.async.bulk.tensor.2d.global.shared::cta.bulk_group.L2::cache_hint [%0, {%2, %3}], [%1], %4;"
               ::"l"(m), "r"(src), "r"(c0), "r"(c1), "l"(pol) : "memory");
}
__device__ __forceinline__ void tma_store_2d_elect(const CUtensorMap* m, uint32_t src, int c0, int c1, uint64_t pol) {
  asm volatile("{\n.reg .pred p;\nelect.sync _|p, 0xffffffff;\n"
               "@p cp.async.bulk.tensor.2d.global.shared::cta.bulk_group.L2::cache_hint [%0, {%2, %3}], [%1], %4;\n"
               "@p cp.async.bulk.commit_group;\n}"
               ::"l"(m), "r"(src), "r"(c0), "r"(c1), "l"(pol) : "memory");
}
__device__ __forceinline__ void bulk_commit() { asm volatile("cp.async.bulk.commit_group;" ::: "memory"); }
template <int NG> __device__ __forceinline__ void bulk_wait_read() { asm volatile("cp.async.bulk.wait_group.read %0;" ::"n"(NG) : "memory"); }
__device__ __forceinline__ void fence_async_smem() { asm volatile("fence.proxy.async.shared::cta;" ::: "memory"); }
__device__ __forceinline__ void wg_fence() { asm volatile("wgmma.fence.sync.aligned;" ::: "memory"); }
__device__ __forceinline__ void wg_commit() { asm volatile("wgmma.commit_group.sync.aligned;" ::: "memory"); }
template <int NG> __device__ __forceinline__ void wg_wait() { asm volatile("wgmma.wait_group.sync.aligned %0;" ::"n"(NG) : "memory"); }
__device__ __forceinline__ void cluster_arrive() { asm volatile("barrier.cluster.arrive.relaxed.aligned;" ::: "memory"); }
__device__ __forceinline__ void cluster_wait() { asm volatile("barrier.cluster.wait.aligned;" ::: "memory"); }
template <int R> __device__ __forceinline__ void reg_inc() { asm volatile("setmaxnreg.inc.sync.aligned.u32 %0;" ::"n"(R)); }
template <int R> __device__ __forceinline__ void reg_dec() { asm volatile("setmaxnreg.dec.sync.aligned.u32 %0;" ::"n"(R)); }
__device__ __forceinline__ void wg_sync(int wg) {
  if (wg == 0) asm volatile("bar.sync 1, 128;" ::: "memory"); else asm volatile("bar.sync 2, 128;" ::: "memory");
}
__device__ __forceinline__ uint32_t mapa(uint32_t a, uint32_t cta) {
  uint32_t r; asm("mapa.shared::cluster.u32 %0, %1, %2;" : "=r"(r) : "r"(a), "r"(cta)); return r;
}
__device__ __forceinline__ uint64_t make_desc(uint32_t addr, uint32_t lbo, uint32_t sbo, uint32_t mode) {
  return (uint64_t)((addr & 0x3FFFF) >> 4) | ((uint64_t)(lbo >> 4) << 16) | ((uint64_t)(sbo >> 4) << 32) | ((uint64_t)mode << 62);
}
__device__ __forceinline__ uint32_t pack_bf16(float lo, float hi) {
  uint32_t r; asm("cvt.rn.bf16x2.f32 %0, %1, %2;" : "=r"(r) : "f"(hi), "f"(lo)); return r;
}
__device__ __forceinline__ void stmatrix_x4(uint32_t addr, uint32_t a, uint32_t b, uint32_t c, uint32_t d) {
  asm volatile("stmatrix.sync.aligned.m8n8.x4.shared.b16 [%0], {%1,%2,%3,%4};" ::"r"(addr), "r"(a), "r"(b), "r"(c), "r"(d) : "memory");
}
__device__ __forceinline__ void prefetch_l2(const void* p) { asm volatile("prefetch.global.L2 [%0];" ::"l"(p) : "memory"); }
__device__ __forceinline__ void wait_clock(uint32_t t0, int d) { while ((int)((uint32_t)clock() - t0) < d) {} }
__device__ __forceinline__ void stg64(unsigned char* p, uint2 v) {
  asm volatile("st.global.v2.u32 [%0], {%1,%2};" ::"l"(p), "r"(v.x), "r"(v.y) : "memory");
}
__device__ __forceinline__ uint2 lds64(uint32_t a) {
  uint2 r; asm volatile("ld.shared.v2.u32 {%0,%1}, [%2];" : "=r"(r.x), "=r"(r.y) : "r"(a) : "memory"); return r;
}
__device__ __forceinline__ uint4 lds128(uint32_t a) {
  uint4 r; asm volatile("ld.shared.v4.u32 {%0,%1,%2,%3}, [%4];" : "=r"(r.x), "=r"(r.y), "=r"(r.z), "=r"(r.w) : "r"(a) : "memory"); return r;
}

template <bool ARM, bool X, bool W>
__device__ __forceinline__ void issue_stage(uint32_t bar, uint32_t xdst, const CUtensorMap* m, int c0, int c1,
                                            uint32_t wdst, const void* wsrc) {
  asm volatile("{\n.reg .pred p, px, pw, pa;\nelect.sync _|p, 0xffffffff;\n"
               "setp.ne.and.u32 pa, %7, 0, p;\nsetp.ne.and.u32 px, %8, 0, p;\nsetp.ne.and.u32 pw, %9, 0, p;\n"
               "@pa mbarrier.arrive.expect_tx.shared::cta.b64 _, [%0], %10;\n"
               "@pw cp.async.bulk.shared::cluster.global.mbarrier::complete_tx::bytes.multicast::cluster [%5], [%6], %11, [%0], %12;\n"
               "@px cp.async.bulk.tensor.2d.shared::cluster.global.mbarrier::complete_tx::bytes [%1], [%2, {%3, %4}], [%0];\n}"
               ::"r"(bar), "r"(xdst), "l"(m), "r"(c0), "r"(c1), "r"(wdst), "l"(wsrc), "n"((int)ARM), "n"((int)X), "n"((int)W),
                 "n"(STB), "n"(WH), "h"((uint16_t)3) : "memory");
}

struct Lut { uint32_t lo[4], hi[4], m4, id; };
__device__ __forceinline__ uint32_t prmt(uint32_t a, uint32_t b, uint32_t s) {
  uint32_t r; asm("prmt.b32 %0, %1, %2, %3;" : "=r"(r) : "r"(a), "r"(b), "r"(s)); return r;
}
__device__ __forceinline__ Lut make_lut(uint4 c0, uint4 c1) {
  Lut l;
  l.lo[0] = prmt(c0.x, c0.y, 0x6420); l.hi[0] = prmt(c0.x, c0.y, 0x7531);
  l.lo[1] = prmt(c0.z, c0.w, 0x6420); l.hi[1] = prmt(c0.z, c0.w, 0x7531);
  l.lo[2] = prmt(c1.x, c1.y, 0x6420); l.hi[2] = prmt(c1.x, c1.y, 0x7531);
  l.lo[3] = prmt(c1.z, c1.w, 0x6420); l.hi[3] = prmt(c1.z, c1.w, 0x7531);
  l.m4 = 0x4444; l.id = 0x3210;
  return l;
}
__device__ __forceinline__ uint2 dequant4(int4 v, const Lut& l, uint2 s) {
  const uint32_t sel = (uint32_t)(v.x + v.y * 16) + (uint32_t)(v.z + v.w * 16) * 256;
  const uint32_t s7 = sel & 0x7777;
  uint32_t s2;
  asm("lop3.b32 %0, %1, %2, %3, 0xEA;" : "=r"(s2) : "r"(sel >> 1), "r"(l.m4), "r"(l.id));
  const uint32_t lo = prmt(prmt(l.lo[0], l.lo[1], s7), prmt(l.lo[2], l.lo[3], s7), s2);
  const uint32_t hi = prmt(prmt(l.hi[0], l.hi[1], s7), prmt(l.hi[2], l.hi[3], s7), s2);
  uint2 r;
  asm("mul.rn.bf16x2 %0, %1, %2;" : "=r"(r.x) : "r"(prmt(lo, hi, 0x5140)), "r"(s.x));
  asm("mul.rn.bf16x2 %0, %1, %2;" : "=r"(r.y) : "r"(prmt(lo, hi, 0x7362)), "r"(s.y));
  return r;
}

template <int B0, int B1>
__device__ __forceinline__ void stage_boxes(const uint32_t (&pk)[56], uint32_t buf, int warp, int lane) {
  const int r = warp * 16 + (lane & 15), ch = lane >> 4;
#pragma unroll
  for (int b = B0; b < B1; b++) {
#pragma unroll
    for (int p = 0; p < 2; p++) {
      const int cc = p * 2 + ch;
      stmatrix_x4(buf + (b - B0) * 4096 + r * 64 + ((cc ^ ((r >> 1) & 3)) << 4),
                  pk[b * 8 + p * 4], pk[b * 8 + p * 4 + 1], pk[b * 8 + p * 4 + 2], pk[b * 8 + p * 4 + 3]);
    }
  }
}

__global__ void __cluster_dims__(2, 1, 1) __launch_bounds__(384, 1)
nf4_gemm_kernel(const int* __restrict__ q, const __nv_bfloat16* __restrict__ cb, const __nv_bfloat16* __restrict__ am,
                unsigned char* __restrict__ gw, const __nv_bfloat16* __restrict__ x,
                const __grid_constant__ TensorMaps maps) {
  const CUtensorMap& mx = maps.x;
  const CUtensorMap& mo = maps.out;
  extern __shared__ __align__(1024) unsigned char smem_raw[];
  const uint32_t sb = smem_u32(smem_raw);
  const uint32_t epi = sb + STAGES * STB, bars = epi + EPI;
  const uint32_t cst = bars + 512, cfull = bars + 192;
  auto full = [&](int s) { return bars + s * 8; };
  auto empty = [&](int s) { return bars + 32 + s * 8; };
  auto jdone = [&](int j) { return bars + 64 + j * 8; };
  unsigned int* gflag = (unsigned int*)(gw + (size_t)K * N * 2);
  unsigned int* gepoch = gflag + 256;

  const int c = blockIdx.x, wid = threadIdx.x >> 5, wg = wid >> 2, lane = threadIdx.x & 31, rank = c & 1;
  const int jc = c >> 1, b7 = jc - 36, k7 = (b7 * 37) >> 8;
  const int gidx = jc < 4 ? 15 : jc < 36 ? ((jc - 4) & 7) : 8 + b7 - 7 * k7;
  const int kidx = jc < 4 ? jc : jc < 36 ? ((jc - 4) >> 3) : k7;
  const int mt = (gidx & 7) * 2 + rank, pj = 4 * (gidx >> 3) + kidx;

  const int grp = mt & 3, r0 = (mt >> 2) * 16 + (lane >> 3);
  const int col = pj * BN + wid * 32 + (lane & 7) * 4;
  const uint32_t cstart = clock();
  wait_clock(cstart, grp * T_JOB0_STEP);
  int4 v[4]; uint4 cb0, cb1; uint2 sc0;
  asm volatile("{\n.reg .pred p;\nsetp.lt.s32 p, %30, 7;\n"
               "@p ld.global.nc.L1::no_allocate.L2::cache_hint.v4.s32 {%0,%1,%2,%3}, [%26], %29;\n"
               "@p ld.global.nc.L1::no_allocate.L2::cache_hint.v4.s32 {%4,%5,%6,%7}, [%26+57344], %29;\n"
               "@p ld.global.nc.L1::no_allocate.L2::cache_hint.v4.s32 {%8,%9,%10,%11}, [%26+114688], %29;\n"
               "@p ld.global.nc.L1::no_allocate.L2::cache_hint.v4.s32 {%12,%13,%14,%15}, [%26+172032], %29;\n"
               "@p ld.global.nc.v4.u32 {%16,%17,%18,%19}, [%27];\n@p ld.global.nc.v4.u32 {%20,%21,%22,%23}, [%27+16];\n"
               "@p ld.global.nc.v2.u32 {%24,%25}, [%28];\n}"
               : "=r"(v[0].x), "=r"(v[0].y), "=r"(v[0].z), "=r"(v[0].w), "=r"(v[1].x), "=r"(v[1].y), "=r"(v[1].z), "=r"(v[1].w),
                 "=r"(v[2].x), "=r"(v[2].y), "=r"(v[2].z), "=r"(v[2].w), "=r"(v[3].x), "=r"(v[3].y), "=r"(v[3].z), "=r"(v[3].w),
                 "=r"(cb0.x), "=r"(cb0.y), "=r"(cb0.z), "=r"(cb0.w), "=r"(cb1.x), "=r"(cb1.y), "=r"(cb1.z), "=r"(cb1.w),
                 "=r"(sc0.x), "=r"(sc0.y)
               : "l"(q + (grp * 64 + r0) * N + col), "l"(cb), "l"(am + col), "l"(EVICT_FIRST), "r"(wid));
  if (threadIdx.x == 288) {
    mbar_init(cfull, 1);
    fence_async_smem();
  } else if (threadIdx.x == 256) {
#pragma unroll
    for (int s = 0; s < STAGES; s++) { mbar_init(full(s), 1); mbar_init(empty(s), 4); }
    asm volatile("fence.mbarrier_init.release.cluster;" ::: "memory");
    fence_async_smem();
  } else if (threadIdx.x == 320) {
#pragma unroll
    for (int j = 0; j < 8; j++) mbar_init(jdone(j), j == 0 ? 7 : 2);
  }
  __syncthreads();
  cluster_arrive();
  const int lo4 = (lane >> 3) * 64 + ((((lane & 7) >> 1) ^ (lane >> 4)) << 4) + (lane & 1) * 8;
  const int hi4 = (lo4 ^ 32) + 256;

  if (wg == 2) {
    reg_dec<REG_SIDE>();
    const int w = __shfl_sync(~0u, wid & 3, 0);
    if (w >= 2) {
      const __nv_bfloat16* xq = x + (size_t)(mt * BM + pj * 16 + (lane & 15)) * K;
      for (int i = w - 2; i < 4; i += 2) { wait_clock(cstart, T_XPF0 + i * T_XPF); if (lane < 16) prefetch_l2(xq + i * BK); }
      mbar_wait(cfull, 0);
      const Lut lut = make_lut(lds128(cst), lds128(cst + 16));
      uint2 sc[7];
#pragma unroll
      for (int g = 0; g < 7; g++) sc[g] = lds64(cst + 32 + g * 64 + (lane & 7) * 8);
      const int rw = r0 + (w - 2) * 8;
#pragma unroll 1
      for (int j = 1; j < 8; j++) {
        const int i = 4 * j + grp;
        wait_clock(cstart, j == 1 ? T_JOB1 + grp * T_JOB1_STEP : T_JOB2 + (i - 8) * T_BLOCK);
        const int* p = q + (size_t)((i & 15) * 64 + rw) * N + (pj + (i >> 4) * 8) * BN + (lane & 7) * 4;
        int4 u[14];
#pragma unroll
        for (int g = 0; g < 14; g++)
          asm volatile("ld.global.nc.L1::no_allocate.L2::cache_hint.v4.s32 {%0,%1,%2,%3}, [%4], %5;"
                       : "=r"(u[g].x), "=r"(u[g].y), "=r"(u[g].z), "=r"(u[g].w)
                       : "l"(p + (size_t)(g / 7) * 4 * N + (g % 7) * 32), "l"(EVICT_FIRST));
        if (j == 4) {
#pragma unroll
          for (int g = 0; g < 7; g++) sc[g] = lds64(cst + 480 + g * 64 + (lane & 7) * 8);
        }
        unsigned char* blk = gw + ((size_t)(pj + (i >> 4) * 8) * KB + (i & 15)) * WB + ((mt >> 2) * 2 + w - 2) * 3584;
#pragma unroll
        for (int g = 0; g < 14; g++)
          *(uint2*)(blk + (g < 7 ? lo4 : hi4) + (g % 7) * 512) = dequant4(u[g], lut, sc[g % 7]);
        __syncwarp();
        if (lane == 0) mbar_arrive(jdone(j));
      }
      cluster_wait();
    } else if (w == 1) {
      if (lane == 0) {
        mbar_expect_tx(cfull, 32 + 2 * 448);
        bulk_load(cst, cb, 32, cfull);
        bulk_load(cst + 32, am + pj * BN, 448, cfull);
        bulk_load(cst + 480, am + (pj + 8) * BN, 448, cfull);
      }
#pragma unroll 1
      for (int j = 0; j < 8; j++) {
        mbar_wait(jdone(j), 0);
        if (lane == 0) asm volatile("red.release.gpu.global.add.u32 [%0], 1;" ::"l"(gflag + pj * 32 + 4 * j + grp) : "memory");
        __syncwarp();
      }
      cluster_wait();
    } else {
      if (lane == 0) asm volatile("prefetch.tensormap [%0];" ::"l"(&mx) : "memory");
      const unsigned int epoch = gepoch[c];
      const unsigned int* fl = gflag + pj * 32 + lane;
      const __nv_bfloat16* xp = x + (size_t)(mt * BM + pj * 16 + (lane & 15)) * K;
      cluster_wait();
      const unsigned int target = (epoch + 1) * 4;
      unsigned int ready = 0;
      int s = 0, ph = 1;
      const unsigned char* wsrc = gw + (size_t)pj * KB * WB + rank * WH;
      auto poll = [&]() {
        unsigned int f;
        asm volatile("ld.relaxed.gpu.global.u32 %0, [%1];" : "=r"(f) : "l"(fl) : "memory");
        return __ballot_sync(~0u, (int)(f - target) >= 0);
      };
      auto acquire = [&]() {
        asm volatile("fence.acquire.gpu;" ::: "memory");
        __syncwarp();
        asm volatile("fence.proxy.async.global;" ::: "memory");
      };
#pragma unroll 1
      for (int i = 0; i < NBLK; i++) {
        const uint32_t xs = sb + s * STB, ws = xs + XB + rank * WH, fb = full(s);
        const int kc = (i & 15) * BK;
        for (int n = 0; n < (1 << 22) && !((ready >> i) & 1) && !mbar_test(empty(s), ph); n++) {
          const unsigned int r = poll();
          if ((r >> i) & 1) { acquire(); ready = r; }
        }
        if ((ready >> i) & 1) {
          if (i == 2 || i == 3) mbar_wait(full(i - 2), 0);
          mbar_wait(empty(s), ph);
          issue_stage<true, true, true>(fb, xs, &mx, kc, mt * BM, ws, wsrc);
        } else {
          mbar_wait(empty(s), ph);
          if (i >= 4) issue_stage<true, true, false>(fb, xs, &mx, kc, mt * BM, ws, wsrc);
          int spins = 0;
          do {
            ready = poll();
            if (++spins > (1 << 22)) asm volatile("trap;");
          } while (!((ready >> i) & 1));
          acquire();
          if (i >= 4) {
            issue_stage<false, false, true>(fb, xs, &mx, kc, mt * BM, ws, wsrc);
          } else {
            if (i >= 2) mbar_wait(full(i - 2), 0);
            issue_stage<true, true, true>(fb, xs, &mx, kc, mt * BM, ws, wsrc);
          }
        }
        if (i + 4 < KB && lane < 16) prefetch_l2(xp + (i + 4) * BK);
        wsrc += (i == KB - 1) ? (size_t)(7 * KB + 1) * WB : (size_t)WB;
        if (++s == STAGES) { s = 0; ph ^= 1; }
      }
      if (lane == 0) gepoch[c] = epoch + 1;
    }
  } else {
    const int widu = __shfl_sync(~0u, wid, 0), warp = widu & 3, wgu = widu >> 2;
    unsigned char* j0lo = gw + (size_t)(pj * KB + grp) * WB + (mt >> 2) * 7168 + wid * 512 + lo4;
    unsigned char* j0hi = j0lo + (hi4 - lo4);
    asm volatile("" : "+l"(j0lo), "+l"(j0hi));
    if (wid < 7) {
      const Lut lut = make_lut(cb0, cb1);
#pragma unroll
      for (int g = 0; g < 4; g++) stg64(((g & 1) ? j0hi : j0lo) + (g >> 1) * 3584, dequant4(v[g], lut, sc0));
      __syncwarp();
      if (lane == 0) mbar_arrive(jdone(0));
    }
    reg_inc<REG_CONSUMER>();
    const bool leader = (threadIdx.x & 127) == 0;
    if (leader) asm volatile("prefetch.tensormap [%0];" ::"l"(&mo) : "memory");
    float acc[112];
    const uint32_t empty_peer = mapa(empty(0), rank ^ 1);
    cluster_wait();
    int s = 0, ph = 0;
    const uint64_t da0 = make_desc(sb + wgu * 8192, 16, 1024, 1), db0 = make_desc(sb + XB, 512, 3584, 2);
    auto mma_block = [&](int first) {
      uint64_t da = da0 + s * (STB >> 4), db = db0 + s * (STB >> 4);
      asm volatile("" : "+l"(da), "+l"(db));
      mbar_wait(full(s), ph);
      wg_fence();
#pragma unroll
      for (int k = 0; k < 4; k++) wgmma_n224(acc, da + k * 2, db + k * 448, !(first && k == 0));
      wg_commit();
    };
    auto release_prev = [&]() {
      const int st = s == 0 ? STAGES - 1 : s - 1;
      if (leader) { mbar_arrive(empty(st)); mbar_arrive_remote(empty_peer + st * 8); }
    };
    auto advance = [&]() { if (++s == STAGES) { s = 0; ph ^= 1; } };

#pragma unroll 1
    for (int kb = 0; kb < KB; kb++) {
      mma_block(kb == 0);
      wg_wait<1>();
      if (kb > 0) release_prev();
      advance();
    }
    wg_wait<0>();
    release_prev();
    uint32_t pk[56];
#pragma unroll
    for (int i = 0; i < 56; i++) pk[i] = pack_bf16(acc[2 * i], acc[2 * i + 1]);

    const uint32_t ebuf = epi + wgu * 24576;
    const int row0 = mt * BM + wgu * 64, col0 = pj * BN, col1 = (pj + 8) * BN;
#pragma unroll
    for (int kb = 0; kb < 7; kb++) {
      mma_block(kb == 0);
      if (kb > 0) { wg_wait<1>(); release_prev(); }
      advance();
      if (kb == 6) { if (leader) bulk_wait_read<5>(); wg_sync(wgu); }
      const uint32_t buf = ebuf + (kb % 6) * 4096;
      if (kb == 0) stage_boxes<0, 1>(pk, buf, warp, lane);
      if (kb == 1) stage_boxes<1, 2>(pk, buf, warp, lane);
      if (kb == 2) stage_boxes<2, 3>(pk, buf, warp, lane);
      if (kb == 3) stage_boxes<3, 4>(pk, buf, warp, lane);
      if (kb == 4) stage_boxes<4, 5>(pk, buf, warp, lane);
      if (kb == 5) stage_boxes<5, 6>(pk, buf, warp, lane);
      if (kb == 6) stage_boxes<6, 7>(pk, buf, warp, lane);
      fence_async_smem();
      wg_sync(wgu);
      if (leader) { tma_store_2d(&mo, buf, col0 + kb * 32, row0, EVICT_FIRST); bulk_commit(); }
    }
#pragma unroll 1
    for (int kb = 7; kb < KB; kb++) {
      const bool hold = kb == KB - 4 && wgu == 1;
      if (hold) { wg_wait<0>(); release_prev(); asm volatile("bar.sync 4, 256;" ::: "memory"); }
      mma_block(0);
      wg_wait<1>();
      if (kb <= KB - 4 && !hold) release_prev();
      if (kb == 10 && leader) bulk_wait_read<0>();
      if (kb == KB - 1 && wgu == 0) asm volatile("bar.arrive 4, 256;" ::: "memory");
      advance();
    }
    wg_wait<0>();
    auto box_buf = [&](int b) { return b < 6 ? ebuf + b * 4096 : sb + wgu * 8192; };
#pragma unroll
    for (int b = 0; b < 7; b++) {
#pragma unroll
      for (int i = b * 8; i < b * 8 + 8; i++) pk[i] = pack_bf16(acc[2 * i], acc[2 * i + 1]);
      const int r = warp * 16 + (lane & 15), ch = lane >> 4;
#pragma unroll
      for (int p = 0; p < 2; p++)
        stmatrix_x4(box_buf(b) + r * 64 + (((p * 2 + ch) ^ ((r >> 1) & 3)) << 4),
                    pk[b * 8 + p * 4], pk[b * 8 + p * 4 + 1], pk[b * 8 + p * 4 + 2], pk[b * 8 + p * 4 + 3]);
      if (b == 1 || b == 3 || b == 6) {
        fence_async_smem();
        wg_sync(wgu);
        const int b0 = b == 1 ? 0 : b == 3 ? 2 : 4;
        if (warp <= b - b0) tma_store_2d_elect(&mo, box_buf(b0 + warp), col1 + (b0 + warp) * 32, row0, EVICT_FIRST);
      }
    }
    bulk_wait_read<0>();
  }
}

__global__ void nf4_gemm_fallback(const int* __restrict__ q, const __nv_bfloat16* __restrict__ cb,
                                  const __nv_bfloat16* __restrict__ am, const __nv_bfloat16* __restrict__ x,
                                  __nv_bfloat16* __restrict__ out) {
  __shared__ float xs[16][BK + 1];
  const int n = blockIdx.x * 128 + threadIdx.x, m0 = blockIdx.y * 16;
  const __nv_bfloat16 scale = am[n];
  float acc[16] = {};
  for (int k0 = 0; k0 < K; k0 += BK) {
    __syncthreads();
    for (int i = threadIdx.x; i < 16 * BK; i += 128) xs[i / BK][i % BK] = __bfloat162float(x[(size_t)(m0 + i / BK) * K + k0 + i % BK]);
    __syncthreads();
    for (int k = 0; k < BK; k++) {
      const float w = __bfloat162float(__hmul(cb[q[(size_t)(k0 + k) * N + n] & 15], scale));
#pragma unroll
      for (int i = 0; i < 16; i++) acc[i] += xs[i][k] * w;
    }
  }
#pragma unroll
  for (int i = 0; i < 16; i++) out[(size_t)(m0 + i) * N + n] = __float2bfloat16(acc[i]);
}

typedef CUresult (*EncodeTiledFn)(CUtensorMap*, CUtensorMapDataType, cuuint32_t, void*, const cuuint64_t*, const cuuint64_t*,
                                  const cuuint32_t*, const cuuint32_t*, CUtensorMapInterleave, CUtensorMapSwizzle,
                                  CUtensorMapL2promotion, CUtensorMapFloatOOBfill);

void make_map_2d(EncodeTiledFn enc, CUtensorMap* m, void* base, uint64_t inner, uint64_t outer, uint32_t b0, uint32_t b1,
                 CUtensorMapSwizzle sw, CUtensorMapL2promotion prom) {
  cuuint64_t dims[2] = {inner, outer};
  cuuint64_t strides[1] = {inner * 2};
  cuuint32_t box[2] = {b0, b1};
  cuuint32_t es[2] = {1, 1};
  enc(m, CU_TENSOR_MAP_DATA_TYPE_BFLOAT16, 2, base, dims, strides, box, es, CU_TENSOR_MAP_INTERLEAVE_NONE, sw, prom,
      CU_TENSOR_MAP_FLOAT_OOB_FILL_NONE);
}

}

extern "C" void kernel_launch(void* const* d_in, const int* in_sizes, int n_in, void* d_out, int out_size) {
  (void)in_sizes; (void)n_in; (void)out_size;
  static EncodeTiledFn enc = nullptr;
  static void* scratch = nullptr;
  static int max_clusters = 0;
  if (!enc) {
    void* f = nullptr;
    cudaDriverEntryPointQueryResult qr;
    cudaGetDriverEntryPoint("cuTensorMapEncodeTiled", &f, cudaEnableDefault, &qr);
    enc = (EncodeTiledFn)f;
    cudaFuncSetAttribute(nf4_gemm_kernel, cudaFuncAttributeMaxDynamicSharedMemorySize, SMEM);
    cudaGetSymbolAddress(&scratch, g_scratch);
    cudaLaunchConfig_t cfg = {};
    cfg.gridDim = dim3(128); cfg.blockDim = dim3(384); cfg.dynamicSmemBytes = SMEM;
    cudaLaunchAttribute attr;
    attr.id = cudaLaunchAttributeClusterDimension;
    attr.val.clusterDim.x = 2; attr.val.clusterDim.y = 1; attr.val.clusterDim.z = 1;
    cfg.attrs = &attr; cfg.numAttrs = 1;
    cudaOccupancyMaxActiveClusters(&max_clusters, nf4_gemm_kernel, &cfg);
  }
  if (max_clusters < 64) {
    nf4_gemm_fallback<<<dim3(N / 128, M / 16), 128, 0, cudaStreamPerThread>>>(
        (const int*)d_in[1], (const __nv_bfloat16*)d_in[2], (const __nv_bfloat16*)d_in[3], (const __nv_bfloat16*)d_in[0],
        (__nv_bfloat16*)d_out);
    return;
  }
  TensorMaps maps;
  make_map_2d(enc, &maps.x, d_in[0], K, M, BK, BM, CU_TENSOR_MAP_SWIZZLE_128B, CU_TENSOR_MAP_L2_PROMOTION_L2_128B);
  make_map_2d(enc, &maps.out, d_out, N, M, 32, 64, CU_TENSOR_MAP_SWIZZLE_64B, CU_TENSOR_MAP_L2_PROMOTION_NONE);
  nf4_gemm_kernel<<<128, 384, SMEM, cudaStreamPerThread>>>(
      (const int*)d_in[1], (const __nv_bfloat16*)d_in[2], (const __nv_bfloat16*)d_in[3], (unsigned char*)scratch,
      (const __nv_bfloat16*)d_in[0], maps);
}
```

```cpp
#include <cuda_runtime.h>
#include <cuda_bf16.h>
#include <cuda.h>
#include <stdint.h>

namespace {

constexpr int M = 2048, N = 3584, K = 1024;
constexpr int BM = 128, BN = 224, BK = 64, KB = K / BK, STAGES = 4, NBLK = 2 * KB;
constexpr int XB = BM * BK * 2, WB = BN * BK * 2, STB = XB + WB, WH = WB / 2;
constexpr int EPI = 49152;
constexpr int SMEM = STAGES * STB + EPI + 512 + 1024;
constexpr int REG_CONSUMER = 200, REG_SIDE = 104;
constexpr int T_JOB0_STEP = 300, T_XPF0 = 1400, T_XPF = 200, T_JOB1 = 2600, T_JOB1_STEP = 350, T_JOB2 = 4200, T_BLOCK = 700;
constexpr int FLAG_STRIDE = 288;
constexpr uint64_t EVICT_FIRST = 0x12F0000000000000ull;

struct alignas(128) TensorMaps { CUtensorMap x, out; };

__device__ __align__(1024) unsigned char g_scratch[(size_t)K * N * 2 + (8 * FLAG_STRIDE + 128) * 4];

__device__ __forceinline__ void wgmma_n224(float (&d)[112], uint64_t da, uint64_t db, int scale_d) {
  asm volatile("{\n.reg .pred p;\nsetp.ne.b32 p, %114, 0;\n"
      "wgmma.mma_async.sync.aligned.m64n224k16.f32.bf16.bf16 {"
      "%0, %1, %2, %3, %4, %5, %6, %7, %8, %9, %10, %11, %12, %13, %14, %15, "
      "%16, %17, %18, %19, %20, %21, %22, %23, %24, %25, %26, %27, %28, %29, %30, %31, "
      "%32, %33, %34, %35, %36, %37, %38, %39, %40, %41, %42, %43, %44, %45, %46, %47, "
      "%48, %49, %50, %51, %52, %53, %54, %55, %56, %57, %58, %59, %60, %61, %62, %63, "
      "%64, %65, %66, %67, %68, %69, %70, %71, %72, %73, %74, %75, %76, %77, %78, %79, "
      "%80, %81, %82, %83, %84, %85, %86, %87, %88, %89, %90, %91, %92, %93, %94, %95, "
      "%96, %97, %98, %99, %100, %101, %102, %103, %104, %105, %106, %107, %108, %109, %110, %111"
      "}, %112, %113, p, 1, 1, 0, 1;\n}\n"
      : "+f"(d[0]), "+f"(d[1]), "+f"(d[2]), "+f"(d[3]), "+f"(d[4]), "+f"(d[5]), "+f"(d[6]), "+f"(d[7]),
      "+f"(d[8]), "+f"(d[9]), "+f"(d[10]), "+f"(d[11]), "+f"(d[12]), "+f"(d[13]), "+f"(d[14]), "+f"(d[15]),
      "+f"(d[16]), "+f"(d[17]), "+f"(d[18]), "+f"(d[19]), "+f"(d[20]), "+f"(d[21]), "+f"(d[22]), "+f"(d[23]),
      "+f"(d[24]), "+f"(d[25]), "+f"(d[26]), "+f"(d[27]), "+f"(d[28]), "+f"(d[29]), "+f"(d[30]), "+f"(d[31]),
      "+f"(d[32]), "+f"(d[33]), "+f"(d[34]), "+f"(d[35]), "+f"(d[36]), "+f"(d[37]), "+f"(d[38]), "+f"(d[39]),
      "+f"(d[40]), "+f"(d[41]), "+f"(d[42]), "+f"(d[43]), "+f"(d[44]), "+f"(d[45]), "+f"(d[46]), "+f"(d[47]),
      "+f"(d[48]), "+f"(d[49]), "+f"(d[50]), "+f"(d[51]), "+f"(d[52]), "+f"(d[53]), "+f"(d[54]), "+f"(d[55]),
      "+f"(d[56]), "+f"(d[57]), "+f"(d[58]), "+f"(d[59]), "+f"(d[60]), "+f"(d[61]), "+f"(d[62]), "+f"(d[63]),
      "+f"(d[64]), "+f"(d[65]), "+f"(d[66]), "+f"(d[67]), "+f"(d[68]), "+f"(d[69]), "+f"(d[70]), "+f"(d[71]),
      "+f"(d[72]), "+f"(d[73]), "+f"(d[74]), "+f"(d[75]), "+f"(d[76]), "+f"(d[77]), "+f"(d[78]), "+f"(d[79]),
      "+f"(d[80]), "+f"(d[81]), "+f"(d[82]), "+f"(d[83]), "+f"(d[84]), "+f"(d[85]), "+f"(d[86]), "+f"(d[87]),
      "+f"(d[88]), "+f"(d[89]), "+f"(d[90]), "+f"(d[91]), "+f"(d[92]), "+f"(d[93]), "+f"(d[94]), "+f"(d[95]),
      "+f"(d[96]), "+f"(d[97]), "+f"(d[98]), "+f"(d[99]), "+f"(d[100]), "+f"(d[101]), "+f"(d[102]), "+f"(d[103]),
      "+f"(d[104]), "+f"(d[105]), "+f"(d[106]), "+f"(d[107]), "+f"(d[108]), "+f"(d[109]), "+f"(d[110]), "+f"(d[111])
      : "l"(da), "l"(db), "r"(scale_d));
}

__device__ __forceinline__ uint32_t smem_u32(const void* p) { return (uint32_t)__cvta_generic_to_shared(p); }
__device__ __forceinline__ void mbar_init(uint32_t bar, uint32_t cnt) {
  asm volatile("mbarrier.init.shared::cta.b64 [%0], %1;" ::"r"(bar), "r"(cnt) : "memory");
}
__device__ __forceinline__ void mbar_expect_tx(uint32_t bar, uint32_t bytes) {
  asm volatile("mbarrier.arrive.expect_tx.shared::cta.b64 _, [%0], %1;" ::"r"(bar), "r"(bytes) : "memory");
}
__device__ __forceinline__ void mbar_arrive(uint32_t bar) {
  asm volatile("mbarrier.arrive.shared::cta.b64 _, [%0];" ::"r"(bar) : "memory");
}
__device__ __forceinline__ void mbar_arrive_remote(uint32_t cluster_addr) {
  asm volatile("mbarrier.arrive.shared::cluster.b64 _, [%0];" ::"r"(cluster_addr) : "memory");
}
__device__ __forceinline__ bool mbar_test(uint32_t bar, uint32_t parity) {
  uint32_t ok;
  asm volatile("{\n.reg .pred p;\nmbarrier.test_wait.parity.shared::cta.b64 p, [%1], %2;\nselp.u32 %0, 1, 0, p;\n}"
               : "=r"(ok) : "r"(bar), "r"(parity) : "memory");
  return ok;
}
__device__ __forceinline__ void mbar_wait(uint32_t bar, uint32_t parity) {
  asm volatile(
      "{\n.reg .pred p;\n.reg .u32 n;\nmov.u32 n, 0;\n"
      "LAB_WAIT:\nmbarrier.try_wait.parity.shared::cta.b64 p, [%0], %1;\n@p bra LAB_DONE;\n"
      "add.u32 n, n, 1;\nsetp.lt.u32 p, n, 1048576;\n@p bra LAB_WAIT;\ntrap;\nLAB_DONE:\n}" ::"r"(bar), "r"(parity) : "memory");
}
__device__ __forceinline__ void bulk_load(uint32_t dst, const void* src, uint32_t bytes, uint32_t bar) {
  asm volatile("cp.async.bulk.shared::cluster.global.mbarrier::complete_tx::bytes [%0], [%1], %2, [%3];"
               ::"r"(dst), "l"(src), "r"(bytes), "r"(bar) : "memory");
}
__device__ __forceinline__ void tma_store_2d(const CUtensorMap* m, uint32_t src, int c0, int c1, uint64_t pol) {
  asm volatile("cp.async.bulk.tensor.2d.global.shared::cta.bulk_group.L2::cache_hint [%0, {%2, %3}], [%1], %4;"
               ::"l"(m), "r"(src), "r"(c0), "r"(c1), "l"(pol) : "memory");
}
__device__ __forceinline__ void tma_store_2d_elect(const CUtensorMap* m, uint32_t src, int c0, int c1, uint64_t pol) {
  asm volatile("{\n.reg .pred p;\nelect.sync _|p, 0xffffffff;\n"
               "@p cp.async.bulk.tensor.2d.global.shared::cta.bulk_group.L2::cache_hint [%0, {%2, %3}], [%1], %4;\n"
               "@p cp.async.bulk.commit_group;\n}"
               ::"l"(m), "r"(src), "r"(c0), "r"(c1), "l"(pol) : "memory");
}
__device__ __forceinline__ void bulk_commit() { asm volatile("cp.async.bulk.commit_group;" ::: "memory"); }
template <int NG> __device__ __forceinline__ void bulk_wait_read() { asm volatile("cp.async.bulk.wait_group.read %0;" ::"n"(NG) : "memory"); }
__device__ __forceinline__ void fence_async_smem() { asm volatile("fence.proxy.async.shared::cta;" ::: "memory"); }
__device__ __forceinline__ void wg_fence() { asm volatile("wgmma.fence.sync.aligned;" ::: "memory"); }
__device__ __forceinline__ void wg_commit() { asm volatile("wgmma.commit_group.sync.aligned;" ::: "memory"); }
template <int NG> __device__ __forceinline__ void wg_wait() { asm volatile("wgmma.wait_group.sync.aligned %0;" ::"n"(NG) : "memory"); }
__device__ __forceinline__ void cluster_arrive() { asm volatile("barrier.cluster.arrive.relaxed.aligned;" ::: "memory"); }
__device__ __forceinline__ void cluster_wait() { asm volatile("barrier.cluster.wait.aligned;" ::: "memory"); }
template <int R> __device__ __forceinline__ void reg_inc() { asm volatile("setmaxnreg.inc.sync.aligned.u32 %0;" ::"n"(R)); }
template <int R> __device__ __forceinline__ void reg_dec() { asm volatile("setmaxnreg.dec.sync.aligned.u32 %0;" ::"n"(R)); }
__device__ __forceinline__ void wg_sync(int wg) {
  if (wg == 0) asm volatile("bar.sync 1, 128;" ::: "memory"); else asm volatile("bar.sync 2, 128;" ::: "memory");
}
__device__ __forceinline__ uint32_t mapa(uint32_t a, uint32_t cta) {
  uint32_t r; asm("mapa.shared::cluster.u32 %0, %1, %2;" : "=r"(r) : "r"(a), "r"(cta)); return r;
}
__device__ __forceinline__ uint64_t make_desc(uint32_t addr, uint32_t lbo, uint32_t sbo, uint32_t mode) {
  return (uint64_t)((addr & 0x3FFFF) >> 4) | ((uint64_t)(lbo >> 4) << 16) | ((uint64_t)(sbo >> 4) << 32) | ((uint64_t)mode << 62);
}
__device__ __forceinline__ uint32_t pack_bf16(float lo, float hi) {
  uint32_t r; asm("cvt.rn.bf16x2.f32 %0, %1, %2;" : "=r"(r) : "f"(hi), "f"(lo)); return r;
}
__device__ __forceinline__ void stmatrix_x4(uint32_t addr, uint32_t a, uint32_t b, uint32_t c, uint32_t d) {
  asm volatile("stmatrix.sync.aligned.m8n8.x4.shared.b16 [%0], {%1,%2,%3,%4};" ::"r"(addr), "r"(a), "r"(b), "r"(c), "r"(d) : "memory");
}
__device__ __forceinline__ void prefetch_l2(const void* p) { asm volatile("prefetch.global.L2 [%0];" ::"l"(p) : "memory"); }
__device__ __forceinline__ void wait_clock(uint32_t t0, int d) { while ((int)((uint32_t)clock() - t0) < d) {} }
__device__ __forceinline__ void stg64(unsigned char* p, uint2 v) {
  asm volatile("st.global.v2.u32 [%0], {%1,%2};" ::"l"(p), "r"(v.x), "r"(v.y) : "memory");
}
__device__ __forceinline__ uint2 lds64(uint32_t a) {
  uint2 r; asm volatile("ld.shared.v2.u32 {%0,%1}, [%2];" : "=r"(r.x), "=r"(r.y) : "r"(a) : "memory"); return r;
}
__device__ __forceinline__ uint4 lds128(uint32_t a) {
  uint4 r; asm volatile("ld.shared.v4.u32 {%0,%1,%2,%3}, [%4];" : "=r"(r.x), "=r"(r.y), "=r"(r.z), "=r"(r.w) : "r"(a) : "memory"); return r;
}

template <bool ARM, bool X, bool W>
__device__ __forceinline__ void issue_stage(uint32_t bar, uint32_t xdst, const CUtensorMap* m, int c0, int c1,
                                            uint32_t wdst, const void* wsrc) {
  asm volatile("{\n.reg .pred p, px, pw, pa;\nelect.sync _|p, 0xffffffff;\n"
               "setp.ne.and.u32 pa, %7, 0, p;\nsetp.ne.and.u32 px, %8, 0, p;\nsetp.ne.and.u32 pw, %9, 0, p;\n"
               "@pa mbarrier.arrive.expect_tx.shared::cta.b64 _, [%0], %10;\n"
               "@pw cp.async.bulk.shared::cluster.global.mbarrier::complete_tx::bytes.multicast::cluster [%5], [%6], %11, [%0], %12;\n"
               "@px cp.async.bulk.tensor.2d.shared::cluster.global.mbarrier::complete_tx::bytes [%1], [%2, {%3, %4}], [%0];\n}"
               ::"r"(bar), "r"(xdst), "l"(m), "r"(c0), "r"(c1), "r"(wdst), "l"(wsrc), "n"((int)ARM), "n"((int)X), "n"((int)W),
                 "n"(STB), "n"(WH), "h"((uint16_t)3) : "memory");
}

struct Lut { uint32_t lo[4], hi[4], m4, id; };
__device__ __forceinline__ uint32_t prmt(uint32_t a, uint32_t b, uint32_t s) {
  uint32_t r; asm("prmt.b32 %0, %1, %2, %3;" : "=r"(r) : "r"(a), "r"(b), "r"(s)); return r;
}
__device__ __forceinline__ Lut make_lut(uint4 c0, uint4 c1) {
  Lut l;
  l.lo[0] = prmt(c0.x, c0.y, 0x6420); l.hi[0] = prmt(c0.x, c0.y, 0x7531);
  l.lo[1] = prmt(c0.z, c0.w, 0x6420); l.hi[1] = prmt(c0.z, c0.w, 0x7531);
  l.lo[2] = prmt(c1.x, c1.y, 0x6420); l.hi[2] = prmt(c1.x, c1.y, 0x7531);
  l.lo[3] = prmt(c1.z, c1.w, 0x6420); l.hi[3] = prmt(c1.z, c1.w, 0x7531);
  l.m4 = 0x4444; l.id = 0x3210;
  return l;
}
__device__ __forceinline__ uint2 dequant4(int4 v, const Lut& l, uint2 s) {
  const uint32_t sel = (uint32_t)(v.x + v.y * 16) + (uint32_t)(v.z + v.w * 16) * 256;
  const uint32_t s7 = sel & 0x7777;
  uint32_t s2;
  asm("lop3.b32 %0, %1, %2, %3, 0xEA;" : "=r"(s2) : "r"(sel >> 1), "r"(l.m4), "r"(l.id));
  const uint32_t lo = prmt(prmt(l.lo[0], l.lo[1], s7), prmt(l.lo[2], l.lo[3], s7), s2);
  const uint32_t hi = prmt(prmt(l.hi[0], l.hi[1], s7), prmt(l.hi[2], l.hi[3], s7), s2);
  uint2 r;
  asm("mul.rn.bf16x2 %0, %1, %2;" : "=r"(r.x) : "r"(prmt(lo, hi, 0x5140)), "r"(s.x));
  asm("mul.rn.bf16x2 %0, %1, %2;" : "=r"(r.y) : "r"(prmt(lo, hi, 0x7362)), "r"(s.y));
  return r;
}

template <int B0, int B1>
__device__ __forceinline__ void stage_boxes(const uint32_t (&pk)[56], uint32_t buf, int warp, int lane) {
  const int r = warp * 16 + (lane & 15), ch = lane >> 4;
#pragma unroll
  for (int b = B0; b < B1; b++) {
#pragma unroll
    for (int p = 0; p < 2; p++) {
      const int cc = p * 2 + ch;
      stmatrix_x4(buf + (b - B0) * 4096 + r * 64 + ((cc ^ ((r >> 1) & 3)) << 4),
                  pk[b * 8 + p * 4], pk[b * 8 + p * 4 + 1], pk[b * 8 + p * 4 + 2], pk[b * 8 + p * 4 + 3]);
    }
  }
}

__global__ void __cluster_dims__(2, 1, 1) __launch_bounds__(384, 1)
nf4_gemm_kernel(const int* __restrict__ q, const __nv_bfloat16* __restrict__ cb, const __nv_bfloat16* __restrict__ am,
                unsigned char* __restrict__ gw, const __nv_bfloat16* __restrict__ x,
                const __grid_constant__ TensorMaps maps) {
  const CUtensorMap& mx = maps.x;
  const CUtensorMap& mo = maps.out;
  extern __shared__ __align__(1024) unsigned char smem_raw[];
  const uint32_t sb = smem_u32(smem_raw);
  const uint32_t epi = sb + STAGES * STB, bars = epi + EPI;
  const uint32_t cst = bars + 512, cfull = bars + 192;
  auto full = [&](int s) { return bars + s * 8; };
  auto empty = [&](int s) { return bars + 32 + s * 8; };
  auto jdone = [&](int j) { return bars + 64 + j * 8; };
  unsigned int* gflag = (unsigned int*)(gw + (size_t)K * N * 2);
  unsigned int* gepoch = gflag + 8 * FLAG_STRIDE;

  const int c = blockIdx.x, wid = threadIdx.x >> 5, wg = wid >> 2, lane = threadIdx.x & 31, rank = c & 1;
  const int jc = c >> 1, b7 = jc - 36, k7 = (b7 * 37) >> 8;
  const int gidx = jc < 4 ? 15 : jc < 36 ? ((jc - 4) & 7) : 8 + b7 - 7 * k7;
  const int kidx = jc < 4 ? jc : jc < 36 ? ((jc - 4) >> 3) : k7;
  const int mt = (gidx & 7) * 2 + rank, pj = 4 * (gidx >> 3) + kidx;

  const int grp = mt & 3, r0 = (mt >> 2) * 16 + (lane >> 3);
  const int col = pj * BN + wid * 32 + (lane & 7) * 4;
  const uint32_t cstart = clock();
  wait_clock(cstart, grp * T_JOB0_STEP);
  int4 v[4]; uint4 cb0, cb1; uint2 sc0;
  asm volatile("{\n.reg .pred p;\nsetp.lt.s32 p, %30, 7;\n"
               "@p ld.global.nc.L1::no_allocate.L2::cache_hint.v4.s32 {%0,%1,%2,%3}, [%26], %29;\n"
               "@p ld.global.nc.L1::no_allocate.L2::cache_hint.v4.s32 {%4,%5,%6,%7}, [%26+57344], %29;\n"
               "@p ld.global.nc.L1::no_allocate.L2::cache_hint.v4.s32 {%8,%9,%10,%11}, [%26+114688], %29;\n"
               "@p ld.global.nc.L1::no_allocate.L2::cache_hint.v4.s32 {%12,%13,%14,%15}, [%26+172032], %29;\n"
               "@p ld.global.nc.v4.u32 {%16,%17,%18,%19}, [%27];\n@p ld.global.nc.v4.u32 {%20,%21,%22,%23}, [%27+16];\n"
               "@p ld.global.nc.v2.u32 {%24,%25}, [%28];\n}"
               : "=r"(v[0].x), "=r"(v[0].y), "=r"(v[0].z), "=r"(v[0].w), "=r"(v[1].x), "=r"(v[1].y), "=r"(v[1].z), "=r"(v[1].w),
                 "=r"(v[2].x), "=r"(v[2].y), "=r"(v[2].z), "=r"(v[2].w), "=r"(v[3].x), "=r"(v[3].y), "=r"(v[3].z), "=r"(v[3].w),
                 "=r"(cb0.x), "=r"(cb0.y), "=r"(cb0.z), "=r"(cb0.w), "=r"(cb1.x), "=r"(cb1.y), "=r"(cb1.z), "=r"(cb1.w),
                 "=r"(sc0.x), "=r"(sc0.y)
               : "l"(q + (grp * 64 + r0) * N + col), "l"(cb), "l"(am + col), "l"(EVICT_FIRST), "r"(wid));
  if (threadIdx.x == 288) {
    mbar_init(cfull, 1);
    fence_async_smem();
  } else if (threadIdx.x == 256) {
#pragma unroll
    for (int s = 0; s < STAGES; s++) { mbar_init(full(s), 1); mbar_init(empty(s), 4); }
    asm volatile("fence.mbarrier_init.release.cluster;" ::: "memory");
    fence_async_smem();
  } else if (threadIdx.x == 320) {
#pragma unroll
    for (int j = 0; j < 8; j++) mbar_init(jdone(j), j == 0 ? 7 : 2);
  }
  __syncthreads();
  cluster_arrive();
  const int lo4 = (lane >> 3) * 64 + ((((lane & 7) >> 1) ^ (lane >> 4)) << 4) + (lane & 1) * 8;
  const int hi4 = (lo4 ^ 32) + 256;

  if (wg == 2) {
    reg_dec<REG_SIDE>();
    const int w = __shfl_sync(~0u, wid & 3, 0);
    if (w >= 2) {
      const __nv_bfloat16* xq = x + (size_t)(mt * BM + pj * 16 + (lane & 15)) * K;
      for (int i = w - 2; i < 4; i += 2) { wait_clock(cstart, T_XPF0 + i * T_XPF); if (lane < 16) prefetch_l2(xq + i * BK); }
      mbar_wait(cfull, 0);
      const Lut lut = make_lut(lds128(cst), lds128(cst + 16));
      uint2 sc[7];
#pragma unroll
      for (int g = 0; g < 7; g++) sc[g] = lds64(cst + 32 + g * 64 + (lane & 7) * 8);
      const int rw = r0 + (w - 2) * 8;
#pragma unroll 1
      for (int j = 1; j < 8; j++) {
        const int i = 4 * j + grp;
        wait_clock(cstart, j == 1 ? T_JOB1 + grp * T_JOB1_STEP : T_JOB2 + (i - 8) * T_BLOCK);
        const int* p = q + (size_t)((i & 15) * 64 + rw) * N + (pj + (i >> 4) * 8) * BN + (lane & 7) * 4;
        int4 u[14];
#pragma unroll
        for (int g = 0; g < 14; g++)
          asm volatile("ld.global.nc.L1::no_allocate.L2::cache_hint.v4.s32 {%0,%1,%2,%3}, [%4], %5;"
                       : "=r"(u[g].x), "=r"(u[g].y), "=r"(u[g].z), "=r"(u[g].w)
                       : "l"(p + (size_t)(g / 7) * 4 * N + (g % 7) * 32), "l"(EVICT_FIRST));
        if (j == 4) {
#pragma unroll
          for (int g = 0; g < 7; g++) sc[g] = lds64(cst + 480 + g * 64 + (lane & 7) * 8);
        }
        unsigned char* blk = gw + ((size_t)(pj + (i >> 4) * 8) * KB + (i & 15)) * WB + ((mt >> 2) * 2 + w - 2) * 3584;
#pragma unroll
        for (int g = 0; g < 14; g++)
          *(uint2*)(blk + (g < 7 ? lo4 : hi4) + (g % 7) * 512) = dequant4(u[g], lut, sc[g % 7]);
        __syncwarp();
        if (lane == 0) mbar_arrive(jdone(j));
      }
      cluster_wait();
    } else if (w == 1) {
      if (lane == 0) {
        mbar_expect_tx(cfull, 32 + 2 * 448);
        bulk_load(cst, cb, 32, cfull);
        bulk_load(cst + 32, am + pj * BN, 448, cfull);
        bulk_load(cst + 480, am + (pj + 8) * BN, 448, cfull);
      }
#pragma unroll 1
      for (int j = 0; j < 8; j++) {
        mbar_wait(jdone(j), 0);
        if (lane == 0) asm volatile("red.release.gpu.global.add.u32 [%0], 1;" ::"l"(gflag + pj * FLAG_STRIDE + 4 * j + grp) : "memory");
        __syncwarp();
      }
      cluster_wait();
    } else {
      if (lane == 0) asm volatile("prefetch.tensormap [%0];" ::"l"(&mx) : "memory");
      const unsigned int epoch = gepoch[c];
      const unsigned int* fl = gflag + pj * FLAG_STRIDE + lane;
      const __nv_bfloat16* xp = x + (size_t)(mt * BM + pj * 16 + (lane & 15)) * K;
      cluster_wait();
      const unsigned int target = (epoch + 1) * 4;
      unsigned int ready = 0;
      int s = 0, ph = 1;
      const unsigned char* wsrc = gw + (size_t)pj * KB * WB + rank * WH;
      auto poll = [&]() {
        unsigned int f;
        asm volatile("ld.relaxed.gpu.global.u32 %0, [%1];" : "=r"(f) : "l"(fl) : "memory");
        return __ballot_sync(~0u, (int)(f - target) >= 0);
      };
      auto acquire = [&]() {
        asm volatile("fence.acquire.gpu;" ::: "memory");
        __syncwarp();
        asm volatile("fence.proxy.async.global;" ::: "memory");
      };
#pragma unroll 1
      for (int i = 0; i < NBLK; i++) {
        const uint32_t xs = sb + s * STB, ws = xs + XB + rank * WH, fb = full(s);
        const int kc = (i & 15) * BK;
        for (int n = 0; n < (1 << 22) && !((ready >> i) & 1) && !mbar_test(empty(s), ph); n++) {
          const unsigned int r = poll();
          if ((r >> i) & 1) { acquire(); ready = r; }
        }
        if ((ready >> i) & 1) {
          if (i == 2 || i == 3) mbar_wait(full(i - 2), 0);
          mbar_wait(empty(s), ph);
          issue_stage<true, true, true>(fb, xs, &mx, kc, mt * BM, ws, wsrc);
        } else {
          mbar_wait(empty(s), ph);
          if (i >= 4) issue_stage<true, true, false>(fb, xs, &mx, kc, mt * BM, ws, wsrc);
          int spins = 0;
          do {
            ready = poll();
            if (++spins > (1 << 22)) asm volatile("trap;");
          } while (!((ready >> i) & 1));
          acquire();
          if (i >= 4) {
            issue_stage<false, false, true>(fb, xs, &mx, kc, mt * BM, ws, wsrc);
          } else {
            if (i >= 2) mbar_wait(full(i - 2), 0);
            issue_stage<true, true, true>(fb, xs, &mx, kc, mt * BM, ws, wsrc);
          }
        }
        if (i + 4 < KB && lane < 16) prefetch_l2(xp + (i + 4) * BK);
        wsrc += (i == KB - 1) ? (size_t)(7 * KB + 1) * WB : (size_t)WB;
        if (++s == STAGES) { s = 0; ph ^= 1; }
      }
      if (lane == 0) gepoch[c] = epoch + 1;
    }
  } else {
    const int widu = __shfl_sync(~0u, wid, 0), warp = widu & 3, wgu = widu >> 2;
    unsigned char* j0lo = gw + (size_t)(pj * KB + grp) * WB + (mt >> 2) * 7168 + wid * 512 + lo4;
    unsigned char* j0hi = j0lo + (hi4 - lo4);
    asm volatile("" : "+l"(j0lo), "+l"(j0hi));
    if (wid < 7) {
      const Lut lut = make_lut(cb0, cb1);
#pragma unroll
      for (int g = 0; g < 4; g++) stg64(((g & 1) ? j0hi : j0lo) + (g >> 1) * 3584, dequant4(v[g], lut, sc0));
      __syncwarp();
      if (lane == 0) mbar_arrive(jdone(0));
    }
    reg_inc<REG_CONSUMER>();
    const bool leader = (threadIdx.x & 127) == 0;
    if (leader) asm volatile("prefetch.tensormap [%0];" ::"l"(&mo) : "memory");
    float acc[112];
    const uint32_t empty_peer = mapa(empty(0), rank ^ 1);
    cluster_wait();
    int s = 0, ph = 0;
    const uint64_t da0 = make_desc(sb + wgu * 8192, 16, 1024, 1), db0 = make_desc(sb + XB, 512, 3584, 2);
    auto mma_block = [&](int first) {
      uint64_t da = da0 + s * (STB >> 4), db = db0 + s * (STB >> 4);
      asm volatile("" : "+l"(da), "+l"(db));
      mbar_wait(full(s), ph);
      wg_fence();
#pragma unroll
      for (int k = 0; k < 4; k++) wgmma_n224(acc, da + k * 2, db + k * 448, !(first && k == 0));
      wg_commit();
    };
    auto release_prev = [&]() {
      const int st = s == 0 ? STAGES - 1 : s - 1;
      if (leader) { mbar_arrive(empty(st)); mbar_arrive_remote(empty_peer + st * 8); }
    };
    auto advance = [&]() { if (++s == STAGES) { s = 0; ph ^= 1; } };

#pragma unroll 1
    for (int kb = 0; kb < KB; kb++) {
      mma_block(kb == 0);
      wg_wait<1>();
      if (kb > 0) release_prev();
      advance();
    }
    wg_wait<0>();
    release_prev();
    uint32_t pk[56];
#pragma unroll
    for (int i = 0; i < 56; i++) pk[i] = pack_bf16(acc[2 * i], acc[2 * i + 1]);

    const uint32_t ebuf = epi + wgu * 24576;
    const int row0 = mt * BM + wgu * 64, col0 = pj * BN, col1 = (pj + 8) * BN;
#pragma unroll
    for (int kb = 0; kb < 7; kb++) {
      mma_block(kb == 0);
      if (kb > 0) { wg_wait<1>(); release_prev(); }
      advance();
      if (kb == 6) { if (leader) bulk_wait_read<5>(); wg_sync(wgu); }
      const uint32_t buf = ebuf + (kb % 6) * 4096;
      if (kb == 0) stage_boxes<0, 1>(pk, buf, warp, lane);
      if (kb == 1) stage_boxes<1, 2>(pk, buf, warp, lane);
      if (kb == 2) stage_boxes<2, 3>(pk, buf, warp, lane);
      if (kb == 3) stage_boxes<3, 4>(pk, buf, warp, lane);
      if (kb == 4) stage_boxes<4, 5>(pk, buf, warp, lane);
      if (kb == 5) stage_boxes<5, 6>(pk, buf, warp, lane);
      if (kb == 6) stage_boxes<6, 7>(pk, buf, warp, lane);
      fence_async_smem();
      wg_sync(wgu);
      if (leader) { tma_store_2d(&mo, buf, col0 + kb * 32, row0, EVICT_FIRST); bulk_commit(); }
    }
#pragma unroll 1
    for (int kb = 7; kb < KB; kb++) {
      const bool hold = kb == KB - 4 && wgu == 1;
      if (hold) { wg_wait<0>(); release_prev(); asm volatile("bar.sync 4, 256;" ::: "memory"); }
      mma_block(0);
      wg_wait<1>();
      if (kb <= KB - 4 && !hold) release_prev();
      if (kb == 10 && leader) bulk_wait_read<0>();
      if (kb == KB - 1 && wgu == 0) asm volatile("bar.arrive 4, 256;" ::: "memory");
      advance();
    }
    wg_wait<0>();
    auto box_buf = [&](int b) { return b < 6 ? ebuf + b * 4096 : sb + wgu * 8192; };
#pragma unroll
    for (int b = 0; b < 7; b++) {
#pragma unroll
      for (int i = b * 8; i < b * 8 + 8; i++) pk[i] = pack_bf16(acc[2 * i], acc[2 * i + 1]);
      const int r = warp * 16 + (lane & 15), ch = lane >> 4;
#pragma unroll
      for (int p = 0; p < 2; p++)
        stmatrix_x4(box_buf(b) + r * 64 + (((p * 2 + ch) ^ ((r >> 1) & 3)) << 4),
                    pk[b * 8 + p * 4], pk[b * 8 + p * 4 + 1], pk[b * 8 + p * 4 + 2], pk[b * 8 + p * 4 + 3]);
      if (b == 1 || b == 3 || b == 6) {
        fence_async_smem();
        wg_sync(wgu);
        const int b0 = b == 1 ? 0 : b == 3 ? 2 : 4;
        if (warp <= b - b0) tma_store_2d_elect(&mo, box_buf(b0 + warp), col1 + (b0 + warp) * 32, row0, EVICT_FIRST);
      }
    }
    bulk_wait_read<0>();
  }
}

__global__ void nf4_gemm_fallback(const int* __restrict__ q, const __nv_bfloat16* __restrict__ cb,
                                  const __nv_bfloat16* __restrict__ am, const __nv_bfloat16* __restrict__ x,
                                  __nv_bfloat16* __restrict__ out) {
  __shared__ float xs[16][BK + 1];
  const int n = blockIdx.x * 128 + threadIdx.x, m0 = blockIdx.y * 16;
  const __nv_bfloat16 scale = am[n];
  float acc[16] = {};
  for (int k0 = 0; k0 < K; k0 += BK) {
    __syncthreads();
    for (int i = threadIdx.x; i < 16 * BK; i += 128) xs[i / BK][i % BK] = __bfloat162float(x[(size_t)(m0 + i / BK) * K + k0 + i % BK]);
    __syncthreads();
    for (int k = 0; k < BK; k++) {
      const float w = __bfloat162float(__hmul(cb[q[(size_t)(k0 + k) * N + n] & 15], scale));
#pragma unroll
      for (int i = 0; i < 16; i++) acc[i] += xs[i][k] * w;
    }
  }
#pragma unroll
  for (int i = 0; i < 16; i++) out[(size_t)(m0 + i) * N + n] = __float2bfloat16(acc[i]);
}

typedef CUresult (*EncodeTiledFn)(CUtensorMap*, CUtensorMapDataType, cuuint32_t, void*, const cuuint64_t*, const cuuint64_t*,
                                  const cuuint32_t*, const cuuint32_t*, CUtensorMapInterleave, CUtensorMapSwizzle,
                                  CUtensorMapL2promotion, CUtensorMapFloatOOBfill);

void make_map_2d(EncodeTiledFn enc, CUtensorMap* m, void* base, uint64_t inner, uint64_t outer, uint32_t b0, uint32_t b1,
                 CUtensorMapSwizzle sw, CUtensorMapL2promotion prom) {
  cuuint64_t dims[2] = {inner, outer};
  cuuint64_t strides[1] = {inner * 2};
  cuuint32_t box[2] = {b0, b1};
  cuuint32_t es[2] = {1, 1};
  enc(m, CU_TENSOR_MAP_DATA_TYPE_BFLOAT16, 2, base, dims, strides, box, es, CU_TENSOR_MAP_INTERLEAVE_NONE, sw, prom,
      CU_TENSOR_MAP_FLOAT_OOB_FILL_NONE);
}

}

extern "C" void kernel_launch(void* const* d_in, const int* in_sizes, int n_in, void* d_out, int out_size) {
  (void)in_sizes; (void)n_in; (void)out_size;
  static EncodeTiledFn enc = nullptr;
  static void* scratch = nullptr;
  static int max_clusters = 0;
  if (!enc) {
    void* f = nullptr;
    cudaDriverEntryPointQueryResult qr;
    cudaGetDriverEntryPoint("cuTensorMapEncodeTiled", &f, cudaEnableDefault, &qr);
    enc = (EncodeTiledFn)f;
    cudaFuncSetAttribute(nf4_gemm_kernel, cudaFuncAttributeMaxDynamicSharedMemorySize, SMEM);
    cudaGetSymbolAddress(&scratch, g_scratch);
    cudaLaunchConfig_t cfg = {};
    cfg.gridDim = dim3(128); cfg.blockDim = dim3(384); cfg.dynamicSmemBytes = SMEM;
    cudaLaunchAttribute attr;
    attr.id = cudaLaunchAttributeClusterDimension;
    attr.val.clusterDim.x = 2; attr.val.clusterDim.y = 1; attr.val.clusterDim.z = 1;
    cfg.attrs = &attr; cfg.numAttrs = 1;
    cudaOccupancyMaxActiveClusters(&max_clusters, nf4_gemm_kernel, &cfg);
  }
  if (max_clusters < 64) {
    nf4_gemm_fallback<<<dim3(N / 128, M / 16), 128, 0, cudaStreamPerThread>>>(
        (const int*)d_in[1], (const __nv_bfloat16*)d_in[2], (const __nv_bfloat16*)d_in[3], (const __nv_bfloat16*)d_in[0],
        (__nv_bfloat16*)d_out);
    return;
  }
  TensorMaps maps;
  make_map_2d(enc, &maps.x, d_in[0], K, M, BK, BM, CU_TENSOR_MAP_SWIZZLE_128B, CU_TENSOR_MAP_L2_PROMOTION_L2_128B);
  make_map_2d(enc, &maps.out, d_out, N, M, 32, 64, CU_TENSOR_MAP_SWIZZLE_64B, CU_TENSOR_MAP_L2_PROMOTION_NONE);
  nf4_gemm_kernel<<<128, 384, SMEM, cudaStreamPerThread>>>(
      (const int*)d_in[1], (const __nv_bfloat16*)d_in[2], (const __nv_bfloat16*)d_in[3], (unsigned char*)scratch,
      (const __nv_bfloat16*)d_in[0], maps);
}
```
